```python
import torch

def _softmax(x, axis=-1):
    return torch.softmax(x, dim=axis)
def _gelu(x):
    return torch.nn.functional.gelu(x, approximate="tanh")
def _silu(x):
    return torch.nn.functional.silu(x)
def _sigmoid(x):
    return torch.sigmoid(x)
def _layernorm(x, axis=-1, eps=1e-5):
    m = x.mean(dim=axis, keepdim=True)
    v = x.var(dim=axis, keepdim=True, unbiased=False)
    return (x - m) / torch.sqrt(v + eps)
def _scatter_add(tgt, idx, src, axis=0):
    return tgt.clone().index_add_(axis, idx, src)
def _segment_sum(src, seg, n):
    out = torch.zeros((n,) + src.shape[1:], dtype=src.dtype)
    return out.index_add_(0, seg, src)
def _pad(x, pw):
    flat = tuple(v for pair in reversed(pw) for v in pair)
    return torch.nn.functional.pad(x, flat)

kernel_name = 'sequential_preLN__softmax_full_mha__dense_activation_gelu__prompt'

def setup_inputs():

    _w = (lambda a: (lambda t: t.to(torch.bfloat16) if t.is_floating_point() else t)(torch.as_tensor(a)))
    def _A_setup():
        B, S, D = 1, 2048, 1024
        return {
            "x": _w((lambda *s: torch.randn(*s, dtype=torch.bfloat16) * 0.05)(B, S, D)),
            "wqkv": _w((lambda *s: torch.randn(*s, dtype=torch.bfloat16) * 0.05)(D, 3 * D)),
            "wo": _w((lambda *s: torch.randn(*s, dtype=torch.bfloat16) * 0.05)(D, D)),
        }
    _A_in = _A_setup()

    def _B_setup():
        B, S, D, F = 1, 2048, 1024, 3584
        return {
            "x": _w((lambda *s: torch.randn(*s, dtype=torch.bfloat16) * 0.05)(B, S, D)),
            "w1": _w((lambda *s: torch.randn(*s, dtype=torch.bfloat16) * 3.2)(D, F) * (D ** -0.5)),
            "b1": _w((lambda *s: torch.randn(*s, dtype=torch.bfloat16) * 3.2)(F) * 0.01),
            "w2": _w((lambda *s: torch.randn(*s, dtype=torch.bfloat16) * 0.4)(F, D) * (F ** -0.5)),
            "b2": _w((lambda *s: torch.randn(*s, dtype=torch.bfloat16) * 0.4)(D) * 0.01),
        }
    _B_in = _B_setup()

    return {
        "A_x": _A_in["x"],
        "A_wqkv": _A_in["wqkv"],
        "A_wo": _A_in["wo"],
        "B_x": _B_in["x"],
        "B_w1": _B_in["w1"],
        "B_b1": _B_in["b1"],
        "B_w2": _B_in["w2"],
        "B_b2": _B_in["b2"],
    }

def reference(A_x, A_wqkv, A_wo, B_x, B_w1, B_b1, B_w2, B_b2):
    def _A_ref(x, wqkv, wo):
        B, S, D = x.shape
        H = 32; Dh = D // H
        qkv = (lambda x, *d: x.permute(*d))((x @ wqkv).reshape(B, S, 3, H, Dh), 2, 0, 3, 1, 4)
        q, k, v = qkv[0], qkv[1], qkv[2]
        scale = Dh ** -0.5
        scores = torch.einsum("bhqd,bhkd->bhqk", q, k) * scale
        p = _softmax(scores, axis=-1)
        o = torch.einsum("bhqk,bhkd->bhqd", p, v)
        return (lambda x, *d: x.permute(*d))(o, 0, 2, 1, 3).reshape(B, S, D) @ wo

    def _B_ref(x, w1, b1, w2, b2):
        h = torch.einsum("bsd,df->bsf", x, w1) + b1
        h = _gelu(h)
        return torch.einsum("bsf,fd->bsd", h, w2) + b2

    x = A_x
    h = x + _A_ref(_layernorm(x, axis=-1), A_wqkv, A_wo)
    h2 = h + _B_ref(_layernorm(h, axis=-1), B_w1, B_b1, B_w2, B_b2)
    return h2
```

```cpp
#include <cuda_runtime.h>
#include <cuda_bf16.h>
#include <cuda.h>
#include <stdint.h>

typedef __nv_bfloat16 bf16;

namespace {

constexpr int SEQ = 2048, DM = 1024, NH = 32, DH = 32, DFF = 3584;

__device__ __align__(1024) bf16 g_xn[SEQ * DM];
__device__ __align__(1024) bf16 g_qkv[3 * NH * SEQ * DH];
__device__ __align__(1024) bf16 g_attn[SEQ * DM];
__device__ __align__(1024) bf16 g_h[SEQ * DM];
__device__ __align__(1024) bf16 g_hn[SEQ * DM];
__device__ __align__(1024) bf16 g_g[SEQ * DFF];

__device__ __forceinline__ uint32_t smem_u32(const void* p) { return (uint32_t)__cvta_generic_to_shared(p); }

__device__ __forceinline__ void mbar_init(uint32_t bar, uint32_t count) {
    asm volatile("mbarrier.init.shared::cta.b64 [%0], %1;" ::"r"(bar), "r"(count) : "memory");
}
__device__ __forceinline__ void mbar_expect_tx(uint32_t bar, uint32_t bytes) {
    asm volatile("mbarrier.arrive.expect_tx.shared::cta.b64 _, [%0], %1;" ::"r"(bar), "r"(bytes) : "memory");
}
__device__ __forceinline__ void mbar_arrive(uint32_t bar) {
    asm volatile("mbarrier.arrive.shared::cta.b64 _, [%0];" ::"r"(bar) : "memory");
}
__device__ __forceinline__ bool mbar_try_wait(uint32_t bar, uint32_t parity) {
    uint32_t ok;
    asm volatile(
        "{\n.reg .pred p;\nmbarrier.try_wait.parity.shared::cta.b64 p, [%1], %2;\nselp.u32 %0, 1, 0, p;\n}\n"
        : "=r"(ok) : "r"(bar), "r"(parity) : "memory");
    return ok;
}
__device__ __forceinline__ void mbar_wait(uint32_t bar, uint32_t parity) {
    if (mbar_try_wait(bar, parity)) return;
    uint32_t it = 0;
    while (!mbar_try_wait(bar, parity)) {
        if (++it > (1u << 24)) __trap();
    }
}
__device__ __forceinline__ void fence_mbar_init() { asm volatile("fence.mbarrier_init.release.cluster;" ::: "memory"); }
__device__ __forceinline__ void fence_proxy_async() { asm volatile("fence.proxy.async.shared::cta;" ::: "memory"); }

__device__ __forceinline__ void tma_load_2d(uint32_t dst, const CUtensorMap* map, int c0, int c1, uint32_t bar) {
    asm volatile("cp.async.bulk.tensor.2d.shared::cluster.global.mbarrier::complete_tx::bytes [%0], [%1, {%3, %4}], [%2];"
                 ::"r"(dst), "l"(map), "r"(bar), "r"(c0), "r"(c1) : "memory");
}
__device__ __forceinline__ void tma_load_3d(uint32_t dst, const CUtensorMap* map, int c0, int c1, int c2, uint32_t bar) {
    asm volatile("cp.async.bulk.tensor.3d.shared::cluster.global.mbarrier::complete_tx::bytes [%0], [%1, {%3, %4, %5}], [%2];"
                 ::"r"(dst), "l"(map), "r"(bar), "r"(c0), "r"(c1), "r"(c2) : "memory");
}
__device__ __forceinline__ void bulk_load(uint32_t dst, const void* src, uint32_t bytes, uint32_t bar) {
    asm volatile("cp.async.bulk.shared::cluster.global.mbarrier::complete_tx::bytes [%0], [%1], %2, [%3];"
                 ::"r"(dst), "l"(src), "r"(bytes), "r"(bar) : "memory");
}
__device__ __forceinline__ void tma_store_2d(const CUtensorMap* map, int c0, int c1, uint32_t src) {
    asm volatile("cp.async.bulk.tensor.2d.global.shared::cta.bulk_group [%0, {%2, %3}], [%1];"
                 ::"l"(map), "r"(src), "r"(c0), "r"(c1) : "memory");
}
__device__ __forceinline__ void bulk_store(void* dst, uint32_t src, uint32_t bytes) {
    asm volatile("cp.async.bulk.global.shared::cta.bulk_group [%0], [%1], %2;" ::"l"(dst), "r"(src), "r"(bytes) : "memory");
}
__device__ __forceinline__ void bulk_commit() { asm volatile("cp.async.bulk.commit_group;" ::: "memory"); }
__device__ __forceinline__ void bulk_wait_read0() { asm volatile("cp.async.bulk.wait_group.read 0;" ::: "memory"); }
__device__ __forceinline__ void bulk_wait0() { asm volatile("cp.async.bulk.wait_group 0;" ::: "memory"); }
__device__ __forceinline__ void prefetch_tmap(const CUtensorMap* map) {
    asm volatile("prefetch.tensormap [%0];" ::"l"(map) : "memory");
}

__device__ __forceinline__ void wgmma_fence() { asm volatile("wgmma.fence.sync.aligned;" ::: "memory"); }
__device__ __forceinline__ void wgmma_commit() { asm volatile("wgmma.commit_group.sync.aligned;" ::: "memory"); }
template <int N> __device__ __forceinline__ void wgmma_wait() { asm volatile("wgmma.wait_group.sync.aligned %0;" ::"n"(N) : "memory"); }

template <int ID> __device__ __forceinline__ void named_bar_sync(int nthreads) {
    asm volatile("bar.sync %0, %1;" ::"n"(ID), "r"(nthreads) : "memory");
}
__device__ __forceinline__ void named_bar_sync_dyn(int id, int nthreads) {
    asm volatile("bar.sync %0, %1;" ::"r"(id), "r"(nthreads) : "memory");
}
template <int R> __device__ __forceinline__ void reg_alloc() { asm volatile("setmaxnreg.inc.sync.aligned.u32 %0;" ::"n"(R)); }
template <int R> __device__ __forceinline__ void reg_dealloc() { asm volatile("setmaxnreg.dec.sync.aligned.u32 %0;" ::"n"(R)); }

__device__ __forceinline__ uint64_t make_desc(uint32_t addr, uint32_t lbo_bytes, uint32_t sbo_bytes, uint32_t swz) {
    return (uint64_t)((addr & 0x3FFFF) >> 4) | ((uint64_t)((lbo_bytes & 0x3FFFF) >> 4) << 16) |
           ((uint64_t)((sbo_bytes & 0x3FFFF) >> 4) << 32) | ((uint64_t)swz << 62);
}

__device__ __forceinline__ uint32_t pack_bf16(float lo, float hi) {
    uint32_t r;
    asm("cvt.rn.bf16x2.f32 %0, %1, %2;" : "=r"(r) : "f"(hi), "f"(lo));
    return r;
}
__device__ __forceinline__ float bf16_lo(uint32_t v) { return __uint_as_float(v << 16); }
__device__ __forceinline__ float bf16_hi(uint32_t v) { return __uint_as_float(v & 0xFFFF0000u); }
__device__ __forceinline__ float ex2(float x) {
    float y;
    asm("ex2.approx.ftz.f32 %0, %1;" : "=f"(y) : "f"(x));
    return y;
}
__device__ __forceinline__ float rcp_approx(float x) {
    float y;
    asm("rcp.approx.ftz.f32 %0, %1;" : "=f"(y) : "f"(x));
    return y;
}
__device__ __forceinline__ void stmatrix_x4(uint32_t addr, uint32_t r0, uint32_t r1, uint32_t r2, uint32_t r3) {
    asm volatile("stmatrix.sync.aligned.m8n8.x4.shared.b16 [%0], {%1, %2, %3, %4};" ::"r"(addr), "r"(r0), "r"(r1), "r"(r2), "r"(r3) : "memory");
}
__device__ __forceinline__ uint32_t lds32(uint32_t addr) {
    uint32_t v;
    asm volatile("ld.shared.b32 %0, [%1];" : "=r"(v) : "r"(addr) : "memory");
    return v;
}
__device__ __forceinline__ void sts32(uint32_t addr, uint32_t v) { asm volatile("st.shared.b32 [%0], %1;" ::"r"(addr), "r"(v) : "memory"); }

__device__ __forceinline__ void wgmma_ss_n64_tb(float (&d)[32], uint64_t da, uint64_t db, int scale_d) {
    asm volatile("{\n.reg .pred p;\nsetp.ne.b32 p, %34, 0;\n"
        "wgmma.mma_async.sync.aligned.m64n64k16.f32.bf16.bf16 {%0, %1, %2, %3, %4, %5, %6, %7, %8, %9, %10, %11, %12, %13, %14, %15, %16, %17, %18, %19, %20, %21, %22, %23, %24, %25, %26, %27, %28, %29, %30, %31}, %32, %33, p, 1, 1, 0, 1;\n}\n"
        : "+f"(d[0]), "+f"(d[1]), "+f"(d[2]), "+f"(d[3]), "+f"(d[4]), "+f"(d[5]), "+f"(d[6]), "+f"(d[7]), "+f"(d[8]), "+f"(d[9]), "+f"(d[10]), "+f"(d[11]), "+f"(d[12]), "+f"(d[13]), "+f"(d[14]), "+f"(d[15]), "+f"(d[16]), "+f"(d[17]), "+f"(d[18]), "+f"(d[19]), "+f"(d[20]), "+f"(d[21]), "+f"(d[22]), "+f"(d[23]), "+f"(d[24]), "+f"(d[25]), "+f"(d[26]), "+f"(d[27]), "+f"(d[28]), "+f"(d[29]), "+f"(d[30]), "+f"(d[31])
        : "l"(da), "l"(db), "r"(scale_d));
}
__device__ __forceinline__ void wgmma_ss_n128_tb(float (&d)[64], uint64_t da, uint64_t db, int scale_d) {
    asm volatile("{\n.reg .pred p;\nsetp.ne.b32 p, %66, 0;\n"
        "wgmma.mma_async.sync.aligned.m64n128k16.f32.bf16.bf16 {%0, %1, %2, %3, %4, %5, %6, %7, %8, %9, %10, %11, %12, %13, %14, %15, %16, %17, %18, %19, %20, %21, %22, %23, %24, %25, %26, %27, %28, %29, %30, %31, %32, %33, %34, %35, %36, %37, %38, %39, %40, %41, %42, %43, %44, %45, %46, %47, %48, %49, %50, %51, %52, %53, %54, %55, %56, %57, %58, %59, %60, %61, %62, %63}, %64, %65, p, 1, 1, 0, 1;\n}\n"
        : "+f"(d[0]), "+f"(d[1]), "+f"(d[2]), "+f"(d[3]), "+f"(d[4]), "+f"(d[5]), "+f"(d[6]), "+f"(d[7]), "+f"(d[8]), "+f"(d[9]), "+f"(d[10]), "+f"(d[11]), "+f"(d[12]), "+f"(d[13]), "+f"(d[14]), "+f"(d[15]), "+f"(d[16]), "+f"(d[17]), "+f"(d[18]), "+f"(d[19]), "+f"(d[20]), "+f"(d[21]), "+f"(d[22]), "+f"(d[23]), "+f"(d[24]), "+f"(d[25]), "+f"(d[26]), "+f"(d[27]), "+f"(d[28]), "+f"(d[29]), "+f"(d[30]), "+f"(d[31]), "+f"(d[32]), "+f"(d[33]), "+f"(d[34]), "+f"(d[35]), "+f"(d[36]), "+f"(d[37]), "+f"(d[38]), "+f"(d[39]), "+f"(d[40]), "+f"(d[41]), "+f"(d[42]), "+f"(d[43]), "+f"(d[44]), "+f"(d[45]), "+f"(d[46]), "+f"(d[47]), "+f"(d[48]), "+f"(d[49]), "+f"(d[50]), "+f"(d[51]), "+f"(d[52]), "+f"(d[53]), "+f"(d[54]), "+f"(d[55]), "+f"(d[56]), "+f"(d[57]), "+f"(d[58]), "+f"(d[59]), "+f"(d[60]), "+f"(d[61]), "+f"(d[62]), "+f"(d[63])
        : "l"(da), "l"(db), "r"(scale_d));
}
__device__ __forceinline__ void wgmma_ss_n192_tb(float (&d)[96], uint64_t da, uint64_t db, int scale_d) {
    asm volatile("{\n.reg .pred p;\nsetp.ne.b32 p, %98, 0;\n"
        "wgmma.mma_async.sync.aligned.m64n192k16.f32.bf16.bf16 {%0, %1, %2, %3, %4, %5, %6, %7, %8, %9, %10, %11, %12, %13, %14, %15, %16, %17, %18, %19, %20, %21, %22, %23, %24, %25, %26, %27, %28, %29, %30, %31, %32, %33, %34, %35, %36, %37, %38, %39, %40, %41, %42, %43, %44, %45, %46, %47, %48, %49, %50, %51, %52, %53, %54, %55, %56, %57, %58, %59, %60, %61, %62, %63, %64, %65, %66, %67, %68, %69, %70, %71, %72, %73, %74, %75, %76, %77, %78, %79, %80, %81, %82, %83, %84, %85, %86, %87, %88, %89, %90, %91, %92, %93, %94, %95}, %96, %97, p, 1, 1, 0, 1;\n}\n"
        : "+f"(d[0]), "+f"(d[1]), "+f"(d[2]), "+f"(d[3]), "+f"(d[4]), "+f"(d[5]), "+f"(d[6]), "+f"(d[7]), "+f"(d[8]), "+f"(d[9]), "+f"(d[10]), "+f"(d[11]), "+f"(d[12]), "+f"(d[13]), "+f"(d[14]), "+f"(d[15]), "+f"(d[16]), "+f"(d[17]), "+f"(d[18]), "+f"(d[19]), "+f"(d[20]), "+f"(d[21]), "+f"(d[22]), "+f"(d[23]), "+f"(d[24]), "+f"(d[25]), "+f"(d[26]), "+f"(d[27]), "+f"(d[28]), "+f"(d[29]), "+f"(d[30]), "+f"(d[31]), "+f"(d[32]), "+f"(d[33]), "+f"(d[34]), "+f"(d[35]), "+f"(d[36]), "+f"(d[37]), "+f"(d[38]), "+f"(d[39]), "+f"(d[40]), "+f"(d[41]), "+f"(d[42]), "+f"(d[43]), "+f"(d[44]), "+f"(d[45]), "+f"(d[46]), "+f"(d[47]), "+f"(d[48]), "+f"(d[49]), "+f"(d[50]), "+f"(d[51]), "+f"(d[52]), "+f"(d[53]), "+f"(d[54]), "+f"(d[55]), "+f"(d[56]), "+f"(d[57]), "+f"(d[58]), "+f"(d[59]), "+f"(d[60]), "+f"(d[61]), "+f"(d[62]), "+f"(d[63]), "+f"(d[64]), "+f"(d[65]), "+f"(d[66]), "+f"(d[67]), "+f"(d[68]), "+f"(d[69]), "+f"(d[70]), "+f"(d[71]), "+f"(d[72]), "+f"(d[73]), "+f"(d[74]), "+f"(d[75]), "+f"(d[76]), "+f"(d[77]), "+f"(d[78]), "+f"(d[79]), "+f"(d[80]), "+f"(d[81]), "+f"(d[82]), "+f"(d[83]), "+f"(d[84]), "+f"(d[85]), "+f"(d[86]), "+f"(d[87]), "+f"(d[88]), "+f"(d[89]), "+f"(d[90]), "+f"(d[91]), "+f"(d[92]), "+f"(d[93]), "+f"(d[94]), "+f"(d[95])
        : "l"(da), "l"(db), "r"(scale_d));
}
__device__ __forceinline__ void wgmma_ss_n256_tb(float (&d)[128], uint64_t da, uint64_t db, int scale_d) {
    asm volatile("{\n.reg .pred p;\nsetp.ne.b32 p, %130, 0;\n"
        "wgmma.mma_async.sync.aligned.m64n256k16.f32.bf16.bf16 {%0, %1, %2, %3, %4, %5, %6, %7, %8, %9, %10, %11, %12, %13, %14, %15, %16, %17, %18, %19, %20, %21, %22, %23, %24, %25, %26, %27, %28, %29, %30, %31, %32, %33, %34, %35, %36, %37, %38, %39, %40, %41, %42, %43, %44, %45, %46, %47, %48, %49, %50, %51, %52, %53, %54, %55, %56, %57, %58, %59, %60, %61, %62, %63, %64, %65, %66, %67, %68, %69, %70, %71, %72, %73, %74, %75, %76, %77, %78, %79, %80, %81, %82, %83, %84, %85, %86, %87, %88, %89, %90, %91, %92, %93, %94, %95, %96, %97, %98, %99, %100, %101, %102, %103, %104, %105, %106, %107, %108, %109, %110, %111, %112, %113, %114, %115, %116, %117, %118, %119, %120, %121, %122, %123, %124, %125, %126, %127}, %128, %129, p, 1, 1, 0, 1;\n}\n"
        : "+f"(d[0]), "+f"(d[1]), "+f"(d[2]), "+f"(d[3]), "+f"(d[4]), "+f"(d[5]), "+f"(d[6]), "+f"(d[7]), "+f"(d[8]), "+f"(d[9]), "+f"(d[10]), "+f"(d[11]), "+f"(d[12]), "+f"(d[13]), "+f"(d[14]), "+f"(d[15]), "+f"(d[16]), "+f"(d[17]), "+f"(d[18]), "+f"(d[19]), "+f"(d[20]), "+f"(d[21]), "+f"(d[22]), "+f"(d[23]), "+f"(d[24]), "+f"(d[25]), "+f"(d[26]), "+f"(d[27]), "+f"(d[28]), "+f"(d[29]), "+f"(d[30]), "+f"(d[31]), "+f"(d[32]), "+f"(d[33]), "+f"(d[34]), "+f"(d[35]), "+f"(d[36]), "+f"(d[37]), "+f"(d[38]), "+f"(d[39]), "+f"(d[40]), "+f"(d[41]), "+f"(d[42]), "+f"(d[43]), "+f"(d[44]), "+f"(d[45]), "+f"(d[46]), "+f"(d[47]), "+f"(d[48]), "+f"(d[49]), "+f"(d[50]), "+f"(d[51]), "+f"(d[52]), "+f"(d[53]), "+f"(d[54]), "+f"(d[55]), "+f"(d[56]), "+f"(d[57]), "+f"(d[58]), "+f"(d[59]), "+f"(d[60]), "+f"(d[61]), "+f"(d[62]), "+f"(d[63]), "+f"(d[64]), "+f"(d[65]), "+f"(d[66]), "+f"(d[67]), "+f"(d[68]), "+f"(d[69]), "+f"(d[70]), "+f"(d[71]), "+f"(d[72]), "+f"(d[73]), "+f"(d[74]), "+f"(d[75]), "+f"(d[76]), "+f"(d[77]), "+f"(d[78]), "+f"(d[79]), "+f"(d[80]), "+f"(d[81]), "+f"(d[82]), "+f"(d[83]), "+f"(d[84]), "+f"(d[85]), "+f"(d[86]), "+f"(d[87]), "+f"(d[88]), "+f"(d[89]), "+f"(d[90]), "+f"(d[91]), "+f"(d[92]), "+f"(d[93]), "+f"(d[94]), "+f"(d[95]), "+f"(d[96]), "+f"(d[97]), "+f"(d[98]), "+f"(d[99]), "+f"(d[100]), "+f"(d[101]), "+f"(d[102]), "+f"(d[103]), "+f"(d[104]), "+f"(d[105]), "+f"(d[106]), "+f"(d[107]), "+f"(d[108]), "+f"(d[109]), "+f"(d[110]), "+f"(d[111]), "+f"(d[112]), "+f"(d[113]), "+f"(d[114]), "+f"(d[115]), "+f"(d[116]), "+f"(d[117]), "+f"(d[118]), "+f"(d[119]), "+f"(d[120]), "+f"(d[121]), "+f"(d[122]), "+f"(d[123]), "+f"(d[124]), "+f"(d[125]), "+f"(d[126]), "+f"(d[127])
        : "l"(da), "l"(db), "r"(scale_d));
}
__device__ __forceinline__ void wgmma_ss_n128(float (&d)[64], uint64_t da, uint64_t db, int scale_d) {
    asm volatile("{\n.reg .pred p;\nsetp.ne.b32 p, %66, 0;\n"
        "wgmma.mma_async.sync.aligned.m64n128k16.f32.bf16.bf16 {%0, %1, %2, %3, %4, %5, %6, %7, %8, %9, %10, %11, %12, %13, %14, %15, %16, %17, %18, %19, %20, %21, %22, %23, %24, %25, %26, %27, %28, %29, %30, %31, %32, %33, %34, %35, %36, %37, %38, %39, %40, %41, %42, %43, %44, %45, %46, %47, %48, %49, %50, %51, %52, %53, %54, %55, %56, %57, %58, %59, %60, %61, %62, %63}, %64, %65, p, 1, 1, 0, 0;\n}\n"
        : "+f"(d[0]), "+f"(d[1]), "+f"(d[2]), "+f"(d[3]), "+f"(d[4]), "+f"(d[5]), "+f"(d[6]), "+f"(d[7]), "+f"(d[8]), "+f"(d[9]), "+f"(d[10]), "+f"(d[11]), "+f"(d[12]), "+f"(d[13]), "+f"(d[14]), "+f"(d[15]), "+f"(d[16]), "+f"(d[17]), "+f"(d[18]), "+f"(d[19]), "+f"(d[20]), "+f"(d[21]), "+f"(d[22]), "+f"(d[23]), "+f"(d[24]), "+f"(d[25]), "+f"(d[26]), "+f"(d[27]), "+f"(d[28]), "+f"(d[29]), "+f"(d[30]), "+f"(d[31]), "+f"(d[32]), "+f"(d[33]), "+f"(d[34]), "+f"(d[35]), "+f"(d[36]), "+f"(d[37]), "+f"(d[38]), "+f"(d[39]), "+f"(d[40]), "+f"(d[41]), "+f"(d[42]), "+f"(d[43]), "+f"(d[44]), "+f"(d[45]), "+f"(d[46]), "+f"(d[47]), "+f"(d[48]), "+f"(d[49]), "+f"(d[50]), "+f"(d[51]), "+f"(d[52]), "+f"(d[53]), "+f"(d[54]), "+f"(d[55]), "+f"(d[56]), "+f"(d[57]), "+f"(d[58]), "+f"(d[59]), "+f"(d[60]), "+f"(d[61]), "+f"(d[62]), "+f"(d[63])
        : "l"(da), "l"(db), "r"(scale_d));
}
__device__ __forceinline__ void wgmma_rs_n40_tb(float (&d)[20], uint32_t a0, uint32_t a1, uint32_t a2, uint32_t a3, uint64_t db, int scale_d) {
    asm volatile("{\n.reg .pred p;\nsetp.ne.b32 p, %25, 0;\n"
        "wgmma.mma_async.sync.aligned.m64n40k16.f32.bf16.bf16 {%0, %1, %2, %3, %4, %5, %6, %7, %8, %9, %10, %11, %12, %13, %14, %15, %16, %17, %18, %19}, {%20, %21, %22, %23}, %24, p, 1, 1, 1;\n}\n"
        : "+f"(d[0]), "+f"(d[1]), "+f"(d[2]), "+f"(d[3]), "+f"(d[4]), "+f"(d[5]), "+f"(d[6]), "+f"(d[7]), "+f"(d[8]), "+f"(d[9]), "+f"(d[10]), "+f"(d[11]), "+f"(d[12]), "+f"(d[13]), "+f"(d[14]), "+f"(d[15]), "+f"(d[16]), "+f"(d[17]), "+f"(d[18]), "+f"(d[19])
        : "r"(a0), "r"(a1), "r"(a2), "r"(a3), "l"(db), "r"(scale_d));
}

template <int N> struct WgmmaSSTB;
template <> struct WgmmaSSTB<64> { static __device__ __forceinline__ void run(float (&d)[32], uint64_t a, uint64_t b, int s) { wgmma_ss_n64_tb(d, a, b, s); } };
template <> struct WgmmaSSTB<128> { static __device__ __forceinline__ void run(float (&d)[64], uint64_t a, uint64_t b, int s) { wgmma_ss_n128_tb(d, a, b, s); } };
template <> struct WgmmaSSTB<192> { static __device__ __forceinline__ void run(float (&d)[96], uint64_t a, uint64_t b, int s) { wgmma_ss_n192_tb(d, a, b, s); } };
template <> struct WgmmaSSTB<256> { static __device__ __forceinline__ void run(float (&d)[128], uint64_t a, uint64_t b, int s) { wgmma_ss_n256_tb(d, a, b, s); } };

__global__ void __launch_bounds__(256) ln_kernel(const bf16* __restrict__ in, bf16* __restrict__ out) {
    const int warp = threadIdx.x >> 5, lane = threadIdx.x & 31;
    const int row = blockIdx.x * 8 + warp;
    const uint4* p = reinterpret_cast<const uint4*>(in + (size_t)row * DM);
    uint4 v[4];
#pragma unroll
    for (int i = 0; i < 4; i++) v[i] = p[lane + 32 * i];
    float f[32];
#pragma unroll
    for (int i = 0; i < 4; i++) {
        const uint32_t w[4] = {v[i].x, v[i].y, v[i].z, v[i].w};
#pragma unroll
        for (int j = 0; j < 4; j++) {
            f[i * 8 + j * 2] = bf16_lo(w[j]);
            f[i * 8 + j * 2 + 1] = bf16_hi(w[j]);
        }
    }
    float s = 0.f;
#pragma unroll
    for (int i = 0; i < 32; i++) s += f[i];
#pragma unroll
    for (int o = 16; o > 0; o >>= 1) s += __shfl_xor_sync(0xffffffffu, s, o);
    const float mean = s * (1.0f / DM);
    float q = 0.f;
#pragma unroll
    for (int i = 0; i < 32; i++) { const float d = f[i] - mean; q += d * d; }
#pragma unroll
    for (int o = 16; o > 0; o >>= 1) q += __shfl_xor_sync(0xffffffffu, q, o);
    const float rstd = 1.0f / sqrtf(q * (1.0f / DM) + 1e-5f);
    uint4* d = reinterpret_cast<uint4*>(out + (size_t)row * DM);
#pragma unroll
    for (int i = 0; i < 4; i++) {
        uint4 w;
        w.x = pack_bf16((f[i * 8 + 0] - mean) * rstd, (f[i * 8 + 1] - mean) * rstd);
        w.y = pack_bf16((f[i * 8 + 2] - mean) * rstd, (f[i * 8 + 3] - mean) * rstd);
        w.z = pack_bf16((f[i * 8 + 4] - mean) * rstd, (f[i * 8 + 5] - mean) * rstd);
        w.w = pack_bf16((f[i * 8 + 6] - mean) * rstd, (f[i * 8 + 7] - mean) * rstd);
        d[lane + 32 * i] = w;
    }
}

enum { EPI_QKV = 0, EPI_RESID = 1, EPI_GELU = 2, EPI_BIAS_RESID = 3 };

template <int BN_, int STAGES_, int EPI_>
struct GemmCfg {
    static constexpr int BM = 128, BK = 64, BN = BN_, STAGES = STAGES_, EPI = EPI_;
    static constexpr int A_BYTES = BM * BK * 2;
    static constexpr int B_BYTES = BK * BN * 2;
    static constexpr int STAGE_BYTES = A_BYTES + B_BYTES;
    static constexpr int STG_BYTES = BM * BN * 2;
    static constexpr int BAR_BYTES = 256;
    static constexpr int SMEM_BYTES = STAGES * STAGE_BYTES + STG_BYTES + BAR_BYTES + 1024;
    static constexpr bool HAS_RESID = (EPI == EPI_RESID || EPI == EPI_BIAS_RESID);
    static constexpr bool HAS_BIAS = (EPI == EPI_GELU || EPI == EPI_BIAS_RESID);
};

__device__ __forceinline__ float gelu_tanh(float x) {
    const float c1 = 2.302208198f;
    const float x2 = x * x;
    const float z = x * c1 * fmaf(0.044715f, x2, 1.0f);
    const float e = ex2(-z);
    return x * rcp_approx(1.0f + e);
}

template <class C>
__global__ void __launch_bounds__(384, 1)
gemm_kernel(const __grid_constant__ CUtensorMap tmA, const __grid_constant__ CUtensorMap tmB,
            const __grid_constant__ CUtensorMap tmC, const __grid_constant__ CUtensorMap tmR,
            const bf16* __restrict__ bias, bf16* __restrict__ out_img, int num_m_blk, int num_n_blk, int k_tiles) {
    extern __shared__ uint8_t smem_raw[];
    const uint32_t smem_base = (smem_u32(smem_raw) + 1023) & ~1023u;
    const uint32_t stg_base = smem_base + C::STAGES * C::STAGE_BYTES;
    const uint32_t bar_base = stg_base + C::STG_BYTES;
    auto full_bar = [&](int s) { return bar_base + 8 * s; };
    auto empty_bar = [&](int s) { return bar_base + 8 * (C::STAGES + s); };
    const uint32_t stg_full = bar_base + 8 * (2 * C::STAGES);
    const uint32_t stg_empty = bar_base + 8 * (2 * C::STAGES + 1);

    const int wg = threadIdx.x >> 7;
    const int warp = (threadIdx.x >> 5) & 3;
    const int lane = threadIdx.x & 31;
    const int num_tiles = num_m_blk * num_n_blk;

    if (threadIdx.x == 0) {
        for (int s = 0; s < C::STAGES; s++) {
            mbar_init(full_bar(s), 1);
            mbar_init(empty_bar(s), 8);
        }
        mbar_init(stg_full, 1);
        mbar_init(stg_empty, 2);
        fence_mbar_init();
        prefetch_tmap(&tmA);
        prefetch_tmap(&tmB);
        if (C::EPI != EPI_QKV) prefetch_tmap(&tmC);
        if (C::HAS_RESID) prefetch_tmap(&tmR);
    }
    __syncthreads();

    if (wg == 0) {
        reg_dealloc<40>();
        if (warp == 0 && lane == 0) {
            int stage = 0;
            uint32_t phase = 0;
            uint32_t stg_phase = 0;
            for (int tile = blockIdx.x; tile < num_tiles; tile += gridDim.x) {
                const int m_blk = tile % num_m_blk, n_blk = tile / num_m_blk;
                const int m0 = m_blk * C::BM, n0 = n_blk * C::BN;
                for (int kt = 0; kt < k_tiles; kt++) {
                    mbar_wait(empty_bar(stage), phase ^ 1);
                    mbar_expect_tx(full_bar(stage), C::STAGE_BYTES);
                    const uint32_t sa = smem_base + stage * C::STAGE_BYTES;
                    tma_load_2d(sa, &tmA, kt * C::BK, m0, full_bar(stage));
                    tma_load_3d(sa + C::A_BYTES, &tmB, 0, kt * C::BK, n0 / 64, full_bar(stage));
                    if (++stage == C::STAGES) { stage = 0; phase ^= 1; }
                }
                if (C::HAS_RESID) {
                    mbar_wait(stg_empty, stg_phase ^ 1);
                    mbar_expect_tx(stg_full, C::STG_BYTES);
#pragma unroll
                    for (int j = 0; j < C::BN / 64; j++)
                        tma_load_2d(stg_base + j * (128 * 128), &tmR, n0 + j * 64, m0, stg_full);
                    stg_phase ^= 1;
                }
            }
        }
    } else {
        reg_alloc<232>();
        const int cw = wg - 1;
        float acc[C::BN / 2];
        int stage = 0;
        uint32_t phase = 0;
        uint32_t stg_phase = 0;
        bool pending_release = false;
        const uint64_t descA0 = make_desc(smem_base + cw * 64 * 128, 16, 1024, 1);
        const uint64_t descB0 = make_desc(smem_base + C::A_BYTES, 64 * 128  , 1024  , 1);

        for (int tile = blockIdx.x; tile < num_tiles; tile += gridDim.x) {
            const int m_blk = tile % num_m_blk, n_blk = tile / num_m_blk;
            const int m0 = m_blk * C::BM, n0 = n_blk * C::BN;
            int prev_stage = 0;
            for (int kt = 0; kt < k_tiles; kt++) {
                mbar_wait(full_bar(stage), phase);
                const uint64_t da = descA0 + (uint64_t)((stage * C::STAGE_BYTES) >> 4);
                const uint64_t db = descB0 + (uint64_t)((stage * C::STAGE_BYTES) >> 4);
                wgmma_fence();
#pragma unroll
                for (int k = 0; k < 4; k++)
                    WgmmaSSTB<C::BN>::run(acc, da + k * 2, db + k * 128, (kt > 0 || k > 0) ? 1 : 0);
                wgmma_commit();
                if (kt > 0) {
                    wgmma_wait<1>();
                    if (lane == 0) mbar_arrive(empty_bar(prev_stage));
                }
                if (C::HAS_RESID && pending_release && kt == 1) {
                    if (warp == 0 && lane == 0) {
                        bulk_wait_read0();
                        mbar_arrive(stg_empty);
                    }
                    pending_release = false;
                }
                prev_stage = stage;
                if (++stage == C::STAGES) { stage = 0; phase ^= 1; }
            }
            wgmma_wait<0>();
            if (lane == 0) mbar_arrive(empty_bar(prev_stage));

            const int row_w = warp * 16;
            if (C::EPI == EPI_QKV) {
                const uint32_t stg = stg_base + cw * (64 * C::BN * 2);
                if (warp == 0 && lane == 0) bulk_wait_read0();
                named_bar_sync_dyn(1 + cw, 128);
                const int r = row_w + (lane & 7) + ((lane >> 3) & 1) * 8;
#pragma unroll
                for (int c16 = 0; c16 < C::BN / 16; c16++) {
                    const int grp = c16 >> 1;
                    const int chunk = (c16 & 1) * 2 + (lane >> 4);
                    const uint32_t addr = stg + grp * 4096 + r * 64 + ((chunk ^ ((r >> 1) & 3)) << 4);
                    stmatrix_x4(addr, pack_bf16(acc[8 * c16 + 0], acc[8 * c16 + 1]), pack_bf16(acc[8 * c16 + 2], acc[8 * c16 + 3]),
                                pack_bf16(acc[8 * c16 + 4], acc[8 * c16 + 5]), pack_bf16(acc[8 * c16 + 6], acc[8 * c16 + 7]));
                }
                fence_proxy_async();
                named_bar_sync_dyn(1 + cw, 128);
                if (warp == 0 && lane == 0) {
#pragma unroll
                    for (int g = 0; g < C::BN / 32; g++) {
                        const int colg = (n0 >> 5) + g;
                        bulk_store(out_img + ((size_t)colg * SEQ + m0 + cw * 64) * DH, stg + g * 4096, 4096);
                    }
                    bulk_commit();
                }
            } else {
                if (C::HAS_RESID) {
                    mbar_wait(stg_full, stg_phase);
                    stg_phase ^= 1;
                    const int r0 = cw * 64 + row_w + (lane >> 2);
                    const int r1 = r0 + 8;
#pragma unroll
                    for (int b = 0; b < C::BN / 8; b++) {
                        const uint32_t box = stg_base + (b >> 3) * (128 * 128);
                        const int chunk = b & 7;
                        const uint32_t a0 = box + r0 * 128 + ((chunk ^ (r0 & 7)) << 4) + (lane & 3) * 4;
                        const uint32_t a1 = box + r1 * 128 + ((chunk ^ (r1 & 7)) << 4) + (lane & 3) * 4;
                        const uint32_t x0 = lds32(a0), x1 = lds32(a1);
                        float v0 = acc[4 * b + 0] + bf16_lo(x0), v1 = acc[4 * b + 1] + bf16_hi(x0);
                        float v2 = acc[4 * b + 2] + bf16_lo(x1), v3 = acc[4 * b + 3] + bf16_hi(x1);
                        if (C::HAS_BIAS) {
                            const uint32_t bb = *reinterpret_cast<const uint32_t*>(bias + n0 + b * 8 + (lane & 3) * 2);
                            v0 += bf16_lo(bb); v1 += bf16_hi(bb); v2 += bf16_lo(bb); v3 += bf16_hi(bb);
                        }
                        sts32(a0, pack_bf16(v0, v1));
                        sts32(a1, pack_bf16(v2, v3));
                    }
                } else {
                    if (warp == 0 && lane == 0) bulk_wait_read0();
                    named_bar_sync_dyn(1 + cw, 128);
                    const int r = cw * 64 + row_w + (lane & 7) + ((lane >> 3) & 1) * 8;
#pragma unroll
                    for (int c16 = 0; c16 < C::BN / 16; c16++) {
                        float v[8];
#pragma unroll
                        for (int i = 0; i < 8; i++) v[i] = acc[8 * c16 + i];
                        if (C::HAS_BIAS) {
                            const uint32_t b0 = *reinterpret_cast<const uint32_t*>(bias + n0 + c16 * 16 + (lane & 3) * 2);
                            const uint32_t b1 = *reinterpret_cast<const uint32_t*>(bias + n0 + c16 * 16 + 8 + (lane & 3) * 2);
                            v[0] += bf16_lo(b0); v[1] += bf16_hi(b0); v[2] += bf16_lo(b0); v[3] += bf16_hi(b0);
                            v[4] += bf16_lo(b1); v[5] += bf16_hi(b1); v[6] += bf16_lo(b1); v[7] += bf16_hi(b1);
                        }
                        if (C::EPI == EPI_GELU) {
#pragma unroll
                            for (int i = 0; i < 8; i++) v[i] = gelu_tanh(v[i]);
                        }
                        const uint32_t box = stg_base + (c16 >> 2) * (128 * 128);
                        const int chunk = (c16 & 3) * 2 + (lane >> 4);
                        const uint32_t addr = box + r * 128 + ((chunk ^ (r & 7)) << 4);
                        stmatrix_x4(addr, pack_bf16(v[0], v[1]), pack_bf16(v[2], v[3]), pack_bf16(v[4], v[5]), pack_bf16(v[6], v[7]));
                    }
                }
                fence_proxy_async();
                named_bar_sync_dyn(1 + cw, 128);
                if (warp == 0 && lane == 0) {
#pragma unroll
                    for (int j = 0; j < C::BN / 64; j++)
                        tma_store_2d(&tmC, n0 + j * 64, m0 + cw * 64, stg_base + j * (128 * 128) + cw * 64 * 128);
                    bulk_commit();
                }
                pending_release = true;
            }
        }
        if (warp == 0 && lane == 0) bulk_wait0();
    }
}

constexpr int ATT_NST = 6;
constexpr int ATT_Q_OFF = 0;
constexpr int ATT_K_OFF = 2 * 8192;
constexpr int ATT_V_OFF = ATT_K_OFF + ATT_NST * 8192;
constexpr int ATT_ONES_OFF = ATT_V_OFF + ATT_NST * 8192;
constexpr int ATT_O_OFF = ATT_ONES_OFF + 8192;
constexpr int ATT_BAR_OFF = ATT_O_OFF + 8192;
constexpr int ATT_SMEM_BYTES = ATT_BAR_OFF + 256 + 1024;

__global__ void __launch_bounds__(384, 1)
attn_kernel(const bf16* __restrict__ qkv, const __grid_constant__ CUtensorMap tmO) {
    extern __shared__ uint8_t smem_raw[];
    const uint32_t smem_base = (smem_u32(smem_raw) + 1023) & ~1023u;
    const uint32_t bar_base = smem_base + ATT_BAR_OFF;
    auto q_full = [&](int b) { return bar_base + 8 * b; };
    auto q_empty = [&](int b) { return bar_base + 8 * (2 + b); };
    auto kv_full = [&](int s) { return bar_base + 8 * (4 + s); };
    auto kv_empty = [&](int s) { return bar_base + 8 * (4 + ATT_NST + s); };

    const int wg = threadIdx.x >> 7;
    const int warp = (threadIdx.x >> 5) & 3;
    const int lane = threadIdx.x & 31;
    constexpr int NUM_UNITS = NH * (SEQ / 128);
    constexpr int NKV = SEQ / 128;

    if (threadIdx.x == 0) {
        for (int b = 0; b < 2; b++) { mbar_init(q_full(b), 1); mbar_init(q_empty(b), 8); }
        for (int s = 0; s < ATT_NST; s++) { mbar_init(kv_full(s), 1); mbar_init(kv_empty(s), 8); }
        fence_mbar_init();
        prefetch_tmap(&tmO);
    }
    for (int i = threadIdx.x; i < 8192 / 4; i += 384) sts32(smem_base + ATT_ONES_OFF + i * 4, 0x3F803F80u);
    fence_proxy_async();
    __syncthreads();

    const bf16* gq = qkv;
    const bf16* gk = qkv + (size_t)NH * SEQ * DH;
    const bf16* gv = qkv + (size_t)2 * NH * SEQ * DH;

    if (wg == 0) {
        reg_dealloc<40>();
        if (warp == 0 && lane == 0) {
            int st = 0; uint32_t ph = 0; int qb = 0; uint32_t qph = 0;
            for (int u = blockIdx.x; u < NUM_UNITS; u += gridDim.x) {
                const int head = u >> 4, qblk = u & 15;
                mbar_wait(q_empty(qb), qph ^ 1);
                mbar_expect_tx(q_full(qb), 8192);
                bulk_load(smem_base + ATT_Q_OFF + qb * 8192, gq + ((size_t)head * SEQ + qblk * 128) * DH, 8192, q_full(qb));
                if (++qb == 2) { qb = 0; qph ^= 1; }
                for (int j = 0; j < NKV; j++) {
                    mbar_wait(kv_empty(st), ph ^ 1);
                    mbar_expect_tx(kv_full(st), 16384);
                    bulk_load(smem_base + ATT_K_OFF + st * 8192, gk + ((size_t)head * SEQ + j * 128) * DH, 8192, kv_full(st));
                    bulk_load(smem_base + ATT_V_OFF + st * 8192, gv + ((size_t)head * SEQ + j * 128) * DH, 8192, kv_full(st));
                    if (++st == ATT_NST) { st = 0; ph ^= 1; }
                }
            }
        }
    } else {
        reg_alloc<232>();
        const int cw = wg - 1;
        const float c = 0.17677669529663687f * 1.4426950408889634f;
        float s0[64], s1[64], o[20];
        uint32_t p[32];
        int st = 0; uint32_t ph = 0;
        int rel = 0;
        int qb = 0; uint32_t qph = 0;
        bool first = true;

        for (int u = blockIdx.x; u < NUM_UNITS; u += gridDim.x) {
            const int head = u >> 4, qblk = u & 15;
            mbar_wait(q_full(qb), qph);
            const uint64_t dq = make_desc(smem_base + ATT_Q_OFF + qb * 8192 + cw * 4096, 16, 512, 2);
            float m0 = -INFINITY, m1 = -INFINITY;
#pragma unroll
            for (int i = 0; i < 20; i++) o[i] = 0.f;

            mbar_wait(kv_full(st), ph);
            {
                const uint64_t dk = make_desc(smem_base + ATT_K_OFF + st * 8192, 16, 512, 2);
                wgmma_fence();
                wgmma_ss_n128(s0, dq, dk, 0);
                wgmma_ss_n128(s0, dq + 2, dk + 2, 1);
                wgmma_commit();
                wgmma_commit();
            }
            int vst = st;
            if (++st == ATT_NST) { st = 0; ph ^= 1; }

            auto step = [&](int j, float (&cur)[64], float (&nxt)[64]) {
                int nst = st;
                if (j + 1 < NKV) {
                    mbar_wait(kv_full(st), ph);
                    const uint64_t dk = make_desc(smem_base + ATT_K_OFF + st * 8192, 16, 512, 2);
                    wgmma_fence();
                    wgmma_ss_n128(nxt, dq, dk, 0);
                    wgmma_ss_n128(nxt, dq + 2, dk + 2, 1);
                    if (++st == ATT_NST) { st = 0; ph ^= 1; }
                }
                wgmma_commit();
                wgmma_wait<2>();
                float mx0 = fmaxf(cur[0], cur[1]), mx1 = fmaxf(cur[2], cur[3]);
#pragma unroll
                for (int b = 1; b < 16; b++) {
                    mx0 = fmaxf(mx0, fmaxf(cur[4 * b], cur[4 * b + 1]));
                    mx1 = fmaxf(mx1, fmaxf(cur[4 * b + 2], cur[4 * b + 3]));
                }
                mx0 = fmaxf(mx0, __shfl_xor_sync(0xffffffffu, mx0, 1));
                mx1 = fmaxf(mx1, __shfl_xor_sync(0xffffffffu, mx1, 1));
                mx0 = fmaxf(mx0, __shfl_xor_sync(0xffffffffu, mx0, 2));
                mx1 = fmaxf(mx1, __shfl_xor_sync(0xffffffffu, mx1, 2));
                const float mn0 = fmaxf(m0, mx0), mn1 = fmaxf(m1, mx1);
                const float a0 = ex2((m0 - mn0) * c), a1 = ex2((m1 - mn1) * c);
                m0 = mn0; m1 = mn1;
                const float mc0 = mn0 * c, mc1 = mn1 * c;
                wgmma_wait<1>();
                if (!(first && j == 0)) {
                    if (j > 0 || true) {
                        if (j > 0 && lane == 0) mbar_arrive(kv_empty(rel));
                    }
                }
                if (j > 0) { if (++rel == ATT_NST) rel = 0; }
#pragma unroll
                for (int i = 0; i < 20; i++) o[i] *= ((i & 2) ? a1 : a0);
#pragma unroll
                for (int b = 0; b < 16; b++) {
                    p[2 * b] = pack_bf16(ex2(fmaf(cur[4 * b], c, -mc0)), ex2(fmaf(cur[4 * b + 1], c, -mc0)));
                    p[2 * b + 1] = pack_bf16(ex2(fmaf(cur[4 * b + 2], c, -mc1)), ex2(fmaf(cur[4 * b + 3], c, -mc1)));
                }
                const uint32_t vbase = smem_base + ATT_V_OFF + vst * 8192;
                const uint64_t dv = make_desc(vbase, (smem_base + ATT_ONES_OFF) - vbase, 512, 2);
                wgmma_fence();
#pragma unroll
                for (int kk = 0; kk < 8; kk++)
                    wgmma_rs_n40_tb(o, p[4 * kk], p[4 * kk + 1], p[4 * kk + 2], p[4 * kk + 3], dv + kk * 64, 1);
                wgmma_commit();
                vst = nst;
            };
#pragma unroll 1
            for (int j = 0; j < NKV; j += 2) {
                step(j, s0, s1);
                step(j + 1, s1, s0);
            }
            wgmma_wait<0>();
            if (lane == 0) {
                mbar_arrive(kv_empty(rel));
                mbar_arrive(q_empty(qb));
            }
            if (++rel == ATT_NST) rel = 0;
            if (++qb == 2) { qb = 0; qph ^= 1; }
            first = false;

            const float inv0 = 1.0f / o[16], inv1 = 1.0f / o[18];
            const uint32_t stg = smem_base + ATT_O_OFF + cw * 4096;
            if (warp == 0 && lane == 0) bulk_wait_read0();
            named_bar_sync_dyn(1 + cw, 128);
            const int r = warp * 16 + (lane & 7) + ((lane >> 3) & 1) * 8;
#pragma unroll
            for (int c16 = 0; c16 < 2; c16++) {
                const int chunk = c16 * 2 + (lane >> 4);
                const uint32_t addr = stg + r * 64 + ((chunk ^ ((r >> 1) & 3)) << 4);
                stmatrix_x4(addr, pack_bf16(o[8 * c16 + 0] * inv0, o[8 * c16 + 1] * inv0), pack_bf16(o[8 * c16 + 2] * inv1, o[8 * c16 + 3] * inv1),
                            pack_bf16(o[8 * c16 + 4] * inv0, o[8 * c16 + 5] * inv0), pack_bf16(o[8 * c16 + 6] * inv1, o[8 * c16 + 7] * inv1));
            }
            fence_proxy_async();
            named_bar_sync_dyn(1 + cw, 128);
            if (warp == 0 && lane == 0) {
                tma_store_2d(&tmO, head * DH, qblk * 128 + cw * 64, stg);
                bulk_commit();
            }
        }
        if (warp == 0 && lane == 0) bulk_wait0();
    }
}

typedef CUresult (*PFN_encodeTiled_t)(CUtensorMap*, CUtensorMapDataType, cuuint32_t, void*, const cuuint64_t*, const cuuint64_t*,
                                      const cuuint32_t*, const cuuint32_t*, CUtensorMapInterleave, CUtensorMapSwizzle,
                                      CUtensorMapL2promotion, CUtensorMapFloatOOBfill);

PFN_encodeTiled_t get_encode_fn() {
    static PFN_encodeTiled_t fn = nullptr;
    if (!fn) {
        void* p = nullptr;
        cudaDriverEntryPointQueryResult q;
        cudaGetDriverEntryPoint("cuTensorMapEncodeTiled", &p, cudaEnableDefault, &q);
        fn = (PFN_encodeTiled_t)p;
    }
    return fn;
}

CUtensorMap make_map_2d(const void* ptr, uint64_t rows, uint64_t cols, uint64_t pitch, uint32_t box_rows, uint32_t box_cols,
                        CUtensorMapSwizzle sw) {
    CUtensorMap m;
    cuuint64_t dims[2] = {cols, rows};
    cuuint64_t strides[1] = {pitch * 2};
    cuuint32_t box[2] = {box_cols, box_rows};
    cuuint32_t es[2] = {1, 1};
    get_encode_fn()(&m, CU_TENSOR_MAP_DATA_TYPE_BFLOAT16, 2, const_cast<void*>(ptr), dims, strides, box, es,
                    CU_TENSOR_MAP_INTERLEAVE_NONE, sw, CU_TENSOR_MAP_L2_PROMOTION_L2_128B, CU_TENSOR_MAP_FLOAT_OOB_FILL_NONE);
    return m;
}
CUtensorMap make_map_w(const void* ptr, uint64_t K, uint64_t N, uint32_t bn) {
    CUtensorMap m;
    cuuint64_t dims[3] = {64, K, N / 64};
    cuuint64_t strides[2] = {N * 2, 128};
    cuuint32_t box[3] = {64, 64, bn / 64};
    cuuint32_t es[3] = {1, 1, 1};
    get_encode_fn()(&m, CU_TENSOR_MAP_DATA_TYPE_BFLOAT16, 3, const_cast<void*>(ptr), dims, strides, box, es,
                    CU_TENSOR_MAP_INTERLEAVE_NONE, CU_TENSOR_MAP_SWIZZLE_128B, CU_TENSOR_MAP_L2_PROMOTION_L2_128B,
                    CU_TENSOR_MAP_FLOAT_OOB_FILL_NONE);
    return m;
}

template <typename T> T* sym_addr(const T& sym) {
    void* p = nullptr;
    cudaGetSymbolAddress(&p, sym);
    return (T*)p;
}

typedef GemmCfg<192, 4, EPI_QKV> CfgQKV;
typedef GemmCfg<128, 5, EPI_RESID> CfgWO;
typedef GemmCfg<256, 3, EPI_GELU> CfgFF1;
typedef GemmCfg<128, 5, EPI_BIAS_RESID> CfgFF2;

}

extern "C" void kernel_launch(void* const* d_in, const int* in_sizes, int n_in, void* d_out, int out_size) {
    (void)in_sizes; (void)n_in; (void)out_size;
    const bf16* x = (const bf16*)d_in[0];
    const bf16* wqkv = (const bf16*)d_in[1];
    const bf16* wo = (const bf16*)d_in[2];
    const bf16* w1 = (const bf16*)d_in[4];
    const bf16* b1 = (const bf16*)d_in[5];
    const bf16* w2 = (const bf16*)d_in[6];
    const bf16* b2 = (const bf16*)d_in[7];
    bf16* out = (bf16*)d_out;

    static bool attr_done = false;
    if (!attr_done) {
        cudaFuncSetAttribute(gemm_kernel<CfgQKV>, cudaFuncAttributeMaxDynamicSharedMemorySize, CfgQKV::SMEM_BYTES);
        cudaFuncSetAttribute(gemm_kernel<CfgWO>, cudaFuncAttributeMaxDynamicSharedMemorySize, CfgWO::SMEM_BYTES);
        cudaFuncSetAttribute(gemm_kernel<CfgFF1>, cudaFuncAttributeMaxDynamicSharedMemorySize, CfgFF1::SMEM_BYTES);
        cudaFuncSetAttribute(gemm_kernel<CfgFF2>, cudaFuncAttributeMaxDynamicSharedMemorySize, CfgFF2::SMEM_BYTES);
        cudaFuncSetAttribute(attn_kernel, cudaFuncAttributeMaxDynamicSharedMemorySize, ATT_SMEM_BYTES);
        attr_done = true;
    }

    bf16* xn = (bf16*)sym_addr(g_xn);
    bf16* qkv = (bf16*)sym_addr(g_qkv);
    bf16* attn = (bf16*)sym_addr(g_attn);
    bf16* h = (bf16*)sym_addr(g_h);
    bf16* hn = (bf16*)sym_addr(g_hn);
    bf16* g = (bf16*)sym_addr(g_g);

    cudaStream_t stream = cudaStreamPerThread;

    ln_kernel<<<SEQ / 8, 256, 0, stream>>>(x, xn);
    {
        CUtensorMap tA = make_map_2d(xn, SEQ, DM, DM, 128, 64, CU_TENSOR_MAP_SWIZZLE_128B);
        CUtensorMap tB = make_map_w(wqkv, DM, 3 * DM, CfgQKV::BN);
        gemm_kernel<CfgQKV><<<132, 384, CfgQKV::SMEM_BYTES, stream>>>(tA, tB, tA, tA, nullptr, qkv, SEQ / 128, 3 * DM / CfgQKV::BN, DM / 64);
    }
    {
        CUtensorMap tO = make_map_2d(attn, SEQ, DM, DM, 64, 32, CU_TENSOR_MAP_SWIZZLE_64B);
        attn_kernel<<<132, 384, ATT_SMEM_BYTES, stream>>>(qkv, tO);
    }
    {
        CUtensorMap tA = make_map_2d(attn, SEQ, DM, DM, 128, 64, CU_TENSOR_MAP_SWIZZLE_128B);
        CUtensorMap tB = make_map_w(wo, DM, DM, CfgWO::BN);
        CUtensorMap tC = make_map_2d(h, SEQ, DM, DM, 64, 64, CU_TENSOR_MAP_SWIZZLE_128B);
        CUtensorMap tR = make_map_2d(x, SEQ, DM, DM, 128, 64, CU_TENSOR_MAP_SWIZZLE_128B);
        gemm_kernel<CfgWO><<<128, 384, CfgWO::SMEM_BYTES, stream>>>(tA, tB, tC, tR, nullptr, nullptr, SEQ / 128, DM / CfgWO::BN, DM / 64);
    }
    ln_kernel<<<SEQ / 8, 256, 0, stream>>>(h, hn);
    {
        CUtensorMap tA = make_map_2d(hn, SEQ, DM, DM, 128, 64, CU_TENSOR_MAP_SWIZZLE_128B);
        CUtensorMap tB = make_map_w(w1, DM, DFF, CfgFF1::BN);
        CUtensorMap tC = make_map_2d(g, SEQ, DFF, DFF, 64, 64, CU_TENSOR_MAP_SWIZZLE_128B);
        gemm_kernel<CfgFF1><<<132, 384, CfgFF1::SMEM_BYTES, stream>>>(tA, tB, tC, tC, b1, nullptr, SEQ / 128, DFF / CfgFF1::BN, DM / 64);
    }
    {
        CUtensorMap tA = make_map_2d(g, SEQ, DFF, DFF, 128, 64, CU_TENSOR_MAP_SWIZZLE_128B);
        CUtensorMap tB = make_map_w(w2, DFF, DM, CfgFF2::BN);
        CUtensorMap tC = make_map_2d(out, SEQ, DM, DM, 64, 64, CU_TENSOR_MAP_SWIZZLE_128B);
        CUtensorMap tR = make_map_2d(h, SEQ, DM, DM, 128, 64, CU_TENSOR_MAP_SWIZZLE_128B);
        gemm_kernel<CfgFF2><<<128, 384, CfgFF2::SMEM_BYTES, stream>>>(tA, tB, tC, tR, b2, nullptr, SEQ / 128, DM / CfgFF2::BN, DFF / 64);
    }
}
```

```cpp
#include <cuda_runtime.h>
#include <cuda_bf16.h>
#include <cuda.h>
#include <stdint.h>

typedef __nv_bfloat16 bf16;

namespace {

constexpr int SEQ = 2048, DM = 1024, NH = 32, DH = 32, DFF = 3584;

__device__ __align__(1024) bf16 g_xn[SEQ * DM];
__device__ __align__(1024) bf16 g_qkv[3 * NH * SEQ * DH];
__device__ __align__(1024) bf16 g_attn[SEQ * DM];
__device__ __align__(1024) bf16 g_h[SEQ * DM];
__device__ __align__(1024) bf16 g_hn[SEQ * DM];
__device__ __align__(1024) bf16 g_g[SEQ * DFF];

#define ATL(slot) do { } while (0)
#define TL(k, slot) do { } while (0)
__device__ __forceinline__ uint32_t smem_u32(const void* p) { return (uint32_t)__cvta_generic_to_shared(p); }

__device__ __forceinline__ void mbar_init(uint32_t bar, uint32_t count) {
    asm volatile("mbarrier.init.shared::cta.b64 [%0], %1;" ::"r"(bar), "r"(count) : "memory");
}
__device__ __forceinline__ void mbar_expect_tx(uint32_t bar, uint32_t bytes) {
    asm volatile("mbarrier.arrive.expect_tx.shared::cta.b64 _, [%0], %1;" ::"r"(bar), "r"(bytes) : "memory");
}
__device__ __forceinline__ void mbar_arrive(uint32_t bar) {
    asm volatile("mbarrier.arrive.shared::cta.b64 _, [%0];" ::"r"(bar) : "memory");
}
__device__ __forceinline__ bool mbar_try_wait(uint32_t bar, uint32_t parity) {
    uint32_t ok;
    asm volatile(
        "{\n.reg .pred p;\nmbarrier.try_wait.parity.shared::cta.b64 p, [%1], %2;\nselp.u32 %0, 1, 0, p;\n}\n"
        : "=r"(ok) : "r"(bar), "r"(parity) : "memory");
    return ok;
}
__device__ __forceinline__ void mbar_wait(uint32_t bar, uint32_t parity) {
    if (mbar_try_wait(bar, parity)) return;
    uint32_t it = 0;
    while (!mbar_try_wait(bar, parity)) {
        if (++it > (1u << 24)) __trap();
    }
}
__device__ __forceinline__ void fence_mbar_init() { asm volatile("fence.mbarrier_init.release.cluster;" ::: "memory"); }
__device__ __forceinline__ void fence_proxy_async() { asm volatile("fence.proxy.async.shared::cta;" ::: "memory"); }

__device__ __forceinline__ void tma_load_2d(uint32_t dst, const CUtensorMap* map, int c0, int c1, uint32_t bar) {
    asm volatile("cp.async.bulk.tensor.2d.shared::cluster.global.mbarrier::complete_tx::bytes [%0], [%1, {%3, %4}], [%2];"
                 ::"r"(dst), "l"(map), "r"(bar), "r"(c0), "r"(c1) : "memory");
}
__device__ __forceinline__ void tma_load_3d(uint32_t dst, const CUtensorMap* map, int c0, int c1, int c2, uint32_t bar) {
    asm volatile("cp.async.bulk.tensor.3d.shared::cluster.global.mbarrier::complete_tx::bytes [%0], [%1, {%3, %4, %5}], [%2];"
                 ::"r"(dst), "l"(map), "r"(bar), "r"(c0), "r"(c1), "r"(c2) : "memory");
}
__device__ __forceinline__ void bulk_load(uint32_t dst, const void* src, uint32_t bytes, uint32_t bar) {
    asm volatile("cp.async.bulk.shared::cluster.global.mbarrier::complete_tx::bytes [%0], [%1], %2, [%3];"
                 ::"r"(dst), "l"(src), "r"(bytes), "r"(bar) : "memory");
}
__device__ __forceinline__ void tma_store_2d(const CUtensorMap* map, int c0, int c1, uint32_t src) {
    asm volatile("cp.async.bulk.tensor.2d.global.shared::cta.bulk_group [%0, {%2, %3}], [%1];"
                 ::"l"(map), "r"(src), "r"(c0), "r"(c1) : "memory");
}
__device__ __forceinline__ void bulk_store(void* dst, uint32_t src, uint32_t bytes) {
    asm volatile("cp.async.bulk.global.shared::cta.bulk_group [%0], [%1], %2;" ::"l"(dst), "r"(src), "r"(bytes) : "memory");
}
__device__ __forceinline__ void bulk_commit() { asm volatile("cp.async.bulk.commit_group;" ::: "memory"); }
__device__ __forceinline__ void bulk_wait_read0() { asm volatile("cp.async.bulk.wait_group.read 0;" ::: "memory"); }
template <int N> __device__ __forceinline__ void bulk_wait_read() { asm volatile("cp.async.bulk.wait_group.read %0;" ::"n"(N) : "memory"); }
__device__ __forceinline__ void bulk_wait0() { asm volatile("cp.async.bulk.wait_group 0;" ::: "memory"); }
__device__ __forceinline__ void prefetch_tmap(const CUtensorMap* map) {
    asm volatile("prefetch.tensormap [%0];" ::"l"(map) : "memory");
}

__device__ __forceinline__ void pdl_launch_dependents() { asm volatile("griddepcontrol.launch_dependents;" ::: "memory"); }
__device__ __forceinline__ void pdl_wait() { asm volatile("griddepcontrol.wait;" ::: "memory"); }

__device__ __forceinline__ void wgmma_fence() { asm volatile("wgmma.fence.sync.aligned;" ::: "memory"); }
__device__ __forceinline__ void wgmma_commit() { asm volatile("wgmma.commit_group.sync.aligned;" ::: "memory"); }
template <int N> __device__ __forceinline__ void wgmma_wait() { asm volatile("wgmma.wait_group.sync.aligned %0;" ::"n"(N) : "memory"); }

template <int ID> __device__ __forceinline__ void named_bar_sync(int nthreads) {
    asm volatile("bar.sync %0, %1;" ::"n"(ID), "r"(nthreads) : "memory");
}
__device__ __forceinline__ void named_bar_sync_dyn(int id, int nthreads) {
    asm volatile("bar.sync %0, %1;" ::"r"(id), "r"(nthreads) : "memory");
}
__device__ __forceinline__ void named_bar_arrive_dyn(int id, int nthreads) {
    asm volatile("bar.arrive %0, %1;" ::"r"(id), "r"(nthreads) : "memory");
}
template <int R> __device__ __forceinline__ void reg_alloc() { asm volatile("setmaxnreg.inc.sync.aligned.u32 %0;" ::"n"(R)); }
template <int R> __device__ __forceinline__ void reg_dealloc() { asm volatile("setmaxnreg.dec.sync.aligned.u32 %0;" ::"n"(R)); }

__device__ __forceinline__ uint64_t make_desc(uint32_t addr, uint32_t lbo_bytes, uint32_t sbo_bytes, uint32_t swz) {
    return (uint64_t)((addr & 0x3FFFF) >> 4) | ((uint64_t)((lbo_bytes & 0x3FFFF) >> 4) << 16) |
           ((uint64_t)((sbo_bytes & 0x3FFFF) >> 4) << 32) | ((uint64_t)swz << 62);
}

__device__ __forceinline__ uint32_t pack_bf16(float lo, float hi) {
    uint32_t r;
    asm("cvt.rn.bf16x2.f32 %0, %1, %2;" : "=r"(r) : "f"(hi), "f"(lo));
    return r;
}
__device__ __forceinline__ float bf16_lo(uint32_t v) { return __uint_as_float(v << 16); }
__device__ __forceinline__ float bf16_hi(uint32_t v) { return __uint_as_float(v & 0xFFFF0000u); }
__device__ __forceinline__ float ex2(float x) {
    float y;
    asm("ex2.approx.ftz.f32 %0, %1;" : "=f"(y) : "f"(x));
    return y;
}
__device__ __forceinline__ float rcp_approx(float x) {
    float y;
    asm("rcp.approx.ftz.f32 %0, %1;" : "=f"(y) : "f"(x));
    return y;
}
__device__ __forceinline__ void stmatrix_x4(uint32_t addr, uint32_t r0, uint32_t r1, uint32_t r2, uint32_t r3) {
    asm volatile("stmatrix.sync.aligned.m8n8.x4.shared.b16 [%0], {%1, %2, %3, %4};" ::"r"(addr), "r"(r0), "r"(r1), "r"(r2), "r"(r3) : "memory");
}
__device__ __forceinline__ uint32_t lds32(uint32_t addr) {
    uint32_t v;
    asm volatile("ld.shared.b32 %0, [%1];" : "=r"(v) : "r"(addr) : "memory");
    return v;
}
__device__ __forceinline__ void sts32(uint32_t addr, uint32_t v) { asm volatile("st.shared.b32 [%0], %1;" ::"r"(addr), "r"(v) : "memory"); }

__device__ __forceinline__ void wgmma_ss_n64_tb(float (&d)[32], uint64_t da, uint64_t db, int scale_d) {
    asm volatile("{\n.reg .pred p;\nsetp.ne.b32 p, %34, 0;\n"
        "wgmma.mma_async.sync.aligned.m64n64k16.f32.bf16.bf16 {%0, %1, %2, %3, %4, %5, %6, %7, %8, %9, %10, %11, %12, %13, %14, %15, %16, %17, %18, %19, %20, %21, %22, %23, %24, %25, %26, %27, %28, %29, %30, %31}, %32, %33, p, 1, 1, 0, 1;\n}\n"
        : "+f"(d[0]), "+f"(d[1]), "+f"(d[2]), "+f"(d[3]), "+f"(d[4]), "+f"(d[5]), "+f"(d[6]), "+f"(d[7]), "+f"(d[8]), "+f"(d[9]), "+f"(d[10]), "+f"(d[11]), "+f"(d[12]), "+f"(d[13]), "+f"(d[14]), "+f"(d[15]), "+f"(d[16]), "+f"(d[17]), "+f"(d[18]), "+f"(d[19]), "+f"(d[20]), "+f"(d[21]), "+f"(d[22]), "+f"(d[23]), "+f"(d[24]), "+f"(d[25]), "+f"(d[26]), "+f"(d[27]), "+f"(d[28]), "+f"(d[29]), "+f"(d[30]), "+f"(d[31])
        : "l"(da), "l"(db), "r"(scale_d));
}
__device__ __forceinline__ void wgmma_ss_n128_tb(float (&d)[64], uint64_t da, uint64_t db, int scale_d) {
    asm volatile("{\n.reg .pred p;\nsetp.ne.b32 p, %66, 0;\n"
        "wgmma.mma_async.sync.aligned.m64n128k16.f32.bf16.bf16 {%0, %1, %2, %3, %4, %5, %6, %7, %8, %9, %10, %11, %12, %13, %14, %15, %16, %17, %18, %19, %20, %21, %22, %23, %24, %25, %26, %27, %28, %29, %30, %31, %32, %33, %34, %35, %36, %37, %38, %39, %40, %41, %42, %43, %44, %45, %46, %47, %48, %49, %50, %51, %52, %53, %54, %55, %56, %57, %58, %59, %60, %61, %62, %63}, %64, %65, p, 1, 1, 0, 1;\n}\n"
        : "+f"(d[0]), "+f"(d[1]), "+f"(d[2]), "+f"(d[3]), "+f"(d[4]), "+f"(d[5]), "+f"(d[6]), "+f"(d[7]), "+f"(d[8]), "+f"(d[9]), "+f"(d[10]), "+f"(d[11]), "+f"(d[12]), "+f"(d[13]), "+f"(d[14]), "+f"(d[15]), "+f"(d[16]), "+f"(d[17]), "+f"(d[18]), "+f"(d[19]), "+f"(d[20]), "+f"(d[21]), "+f"(d[22]), "+f"(d[23]), "+f"(d[24]), "+f"(d[25]), "+f"(d[26]), "+f"(d[27]), "+f"(d[28]), "+f"(d[29]), "+f"(d[30]), "+f"(d[31]), "+f"(d[32]), "+f"(d[33]), "+f"(d[34]), "+f"(d[35]), "+f"(d[36]), "+f"(d[37]), "+f"(d[38]), "+f"(d[39]), "+f"(d[40]), "+f"(d[41]), "+f"(d[42]), "+f"(d[43]), "+f"(d[44]), "+f"(d[45]), "+f"(d[46]), "+f"(d[47]), "+f"(d[48]), "+f"(d[49]), "+f"(d[50]), "+f"(d[51]), "+f"(d[52]), "+f"(d[53]), "+f"(d[54]), "+f"(d[55]), "+f"(d[56]), "+f"(d[57]), "+f"(d[58]), "+f"(d[59]), "+f"(d[60]), "+f"(d[61]), "+f"(d[62]), "+f"(d[63])
        : "l"(da), "l"(db), "r"(scale_d));
}
__device__ __forceinline__ void wgmma_ss_n192_tb(float (&d)[96], uint64_t da, uint64_t db, int scale_d) {
    asm volatile("{\n.reg .pred p;\nsetp.ne.b32 p, %98, 0;\n"
        "wgmma.mma_async.sync.aligned.m64n192k16.f32.bf16.bf16 {%0, %1, %2, %3, %4, %5, %6, %7, %8, %9, %10, %11, %12, %13, %14, %15, %16, %17, %18, %19, %20, %21, %22, %23, %24, %25, %26, %27, %28, %29, %30, %31, %32, %33, %34, %35, %36, %37, %38, %39, %40, %41, %42, %43, %44, %45, %46, %47, %48, %49, %50, %51, %52, %53, %54, %55, %56, %57, %58, %59, %60, %61, %62, %63, %64, %65, %66, %67, %68, %69, %70, %71, %72, %73, %74, %75, %76, %77, %78, %79, %80, %81, %82, %83, %84, %85, %86, %87, %88, %89, %90, %91, %92, %93, %94, %95}, %96, %97, p, 1, 1, 0, 1;\n}\n"
        : "+f"(d[0]), "+f"(d[1]), "+f"(d[2]), "+f"(d[3]), "+f"(d[4]), "+f"(d[5]), "+f"(d[6]), "+f"(d[7]), "+f"(d[8]), "+f"(d[9]), "+f"(d[10]), "+f"(d[11]), "+f"(d[12]), "+f"(d[13]), "+f"(d[14]), "+f"(d[15]), "+f"(d[16]), "+f"(d[17]), "+f"(d[18]), "+f"(d[19]), "+f"(d[20]), "+f"(d[21]), "+f"(d[22]), "+f"(d[23]), "+f"(d[24]), "+f"(d[25]), "+f"(d[26]), "+f"(d[27]), "+f"(d[28]), "+f"(d[29]), "+f"(d[30]), "+f"(d[31]), "+f"(d[32]), "+f"(d[33]), "+f"(d[34]), "+f"(d[35]), "+f"(d[36]), "+f"(d[37]), "+f"(d[38]), "+f"(d[39]), "+f"(d[40]), "+f"(d[41]), "+f"(d[42]), "+f"(d[43]), "+f"(d[44]), "+f"(d[45]), "+f"(d[46]), "+f"(d[47]), "+f"(d[48]), "+f"(d[49]), "+f"(d[50]), "+f"(d[51]), "+f"(d[52]), "+f"(d[53]), "+f"(d[54]), "+f"(d[55]), "+f"(d[56]), "+f"(d[57]), "+f"(d[58]), "+f"(d[59]), "+f"(d[60]), "+f"(d[61]), "+f"(d[62]), "+f"(d[63]), "+f"(d[64]), "+f"(d[65]), "+f"(d[66]), "+f"(d[67]), "+f"(d[68]), "+f"(d[69]), "+f"(d[70]), "+f"(d[71]), "+f"(d[72]), "+f"(d[73]), "+f"(d[74]), "+f"(d[75]), "+f"(d[76]), "+f"(d[77]), "+f"(d[78]), "+f"(d[79]), "+f"(d[80]), "+f"(d[81]), "+f"(d[82]), "+f"(d[83]), "+f"(d[84]), "+f"(d[85]), "+f"(d[86]), "+f"(d[87]), "+f"(d[88]), "+f"(d[89]), "+f"(d[90]), "+f"(d[91]), "+f"(d[92]), "+f"(d[93]), "+f"(d[94]), "+f"(d[95])
        : "l"(da), "l"(db), "r"(scale_d));
}
__device__ __forceinline__ void wgmma_ss_n224_tb(float (&d)[112], uint64_t da, uint64_t db, int scale_d) {
    asm volatile("{\n.reg .pred p;\nsetp.ne.b32 p, %114, 0;\n"
        "wgmma.mma_async.sync.aligned.m64n224k16.f32.bf16.bf16 {%0, %1, %2, %3, %4, %5, %6, %7, %8, %9, %10, %11, %12, %13, %14, %15, %16, %17, %18, %19, %20, %21, %22, %23, %24, %25, %26, %27, %28, %29, %30, %31, %32, %33, %34, %35, %36, %37, %38, %39, %40, %41, %42, %43, %44, %45, %46, %47, %48, %49, %50, %51, %52, %53, %54, %55, %56, %57, %58, %59, %60, %61, %62, %63, %64, %65, %66, %67, %68, %69, %70, %71, %72, %73, %74, %75, %76, %77, %78, %79, %80, %81, %82, %83, %84, %85, %86, %87, %88, %89, %90, %91, %92, %93, %94, %95, %96, %97, %98, %99, %100, %101, %102, %103, %104, %105, %106, %107, %108, %109, %110, %111}, %112, %113, p, 1, 1, 0, 1;\n}\n"
        : "+f"(d[0]), "+f"(d[1]), "+f"(d[2]), "+f"(d[3]), "+f"(d[4]), "+f"(d[5]), "+f"(d[6]), "+f"(d[7]), "+f"(d[8]), "+f"(d[9]), "+f"(d[10]), "+f"(d[11]), "+f"(d[12]), "+f"(d[13]), "+f"(d[14]), "+f"(d[15]), "+f"(d[16]), "+f"(d[17]), "+f"(d[18]), "+f"(d[19]), "+f"(d[20]), "+f"(d[21]), "+f"(d[22]), "+f"(d[23]), "+f"(d[24]), "+f"(d[25]), "+f"(d[26]), "+f"(d[27]), "+f"(d[28]), "+f"(d[29]), "+f"(d[30]), "+f"(d[31]), "+f"(d[32]), "+f"(d[33]), "+f"(d[34]), "+f"(d[35]), "+f"(d[36]), "+f"(d[37]), "+f"(d[38]), "+f"(d[39]), "+f"(d[40]), "+f"(d[41]), "+f"(d[42]), "+f"(d[43]), "+f"(d[44]), "+f"(d[45]), "+f"(d[46]), "+f"(d[47]), "+f"(d[48]), "+f"(d[49]), "+f"(d[50]), "+f"(d[51]), "+f"(d[52]), "+f"(d[53]), "+f"(d[54]), "+f"(d[55]), "+f"(d[56]), "+f"(d[57]), "+f"(d[58]), "+f"(d[59]), "+f"(d[60]), "+f"(d[61]), "+f"(d[62]), "+f"(d[63]), "+f"(d[64]), "+f"(d[65]), "+f"(d[66]), "+f"(d[67]), "+f"(d[68]), "+f"(d[69]), "+f"(d[70]), "+f"(d[71]), "+f"(d[72]), "+f"(d[73]), "+f"(d[74]), "+f"(d[75]), "+f"(d[76]), "+f"(d[77]), "+f"(d[78]), "+f"(d[79]), "+f"(d[80]), "+f"(d[81]), "+f"(d[82]), "+f"(d[83]), "+f"(d[84]), "+f"(d[85]), "+f"(d[86]), "+f"(d[87]), "+f"(d[88]), "+f"(d[89]), "+f"(d[90]), "+f"(d[91]), "+f"(d[92]), "+f"(d[93]), "+f"(d[94]), "+f"(d[95]), "+f"(d[96]), "+f"(d[97]), "+f"(d[98]), "+f"(d[99]), "+f"(d[100]), "+f"(d[101]), "+f"(d[102]), "+f"(d[103]), "+f"(d[104]), "+f"(d[105]), "+f"(d[106]), "+f"(d[107]), "+f"(d[108]), "+f"(d[109]), "+f"(d[110]), "+f"(d[111])
        : "l"(da), "l"(db), "r"(scale_d));
}
__device__ __forceinline__ void wgmma_ss_n256_tb(float (&d)[128], uint64_t da, uint64_t db, int scale_d) {
    asm volatile("{\n.reg .pred p;\nsetp.ne.b32 p, %130, 0;\n"
        "wgmma.mma_async.sync.aligned.m64n256k16.f32.bf16.bf16 {%0, %1, %2, %3, %4, %5, %6, %7, %8, %9, %10, %11, %12, %13, %14, %15, %16, %17, %18, %19, %20, %21, %22, %23, %24, %25, %26, %27, %28, %29, %30, %31, %32, %33, %34, %35, %36, %37, %38, %39, %40, %41, %42, %43, %44, %45, %46, %47, %48, %49, %50, %51, %52, %53, %54, %55, %56, %57, %58, %59, %60, %61, %62, %63, %64, %65, %66, %67, %68, %69, %70, %71, %72, %73, %74, %75, %76, %77, %78, %79, %80, %81, %82, %83, %84, %85, %86, %87, %88, %89, %90, %91, %92, %93, %94, %95, %96, %97, %98, %99, %100, %101, %102, %103, %104, %105, %106, %107, %108, %109, %110, %111, %112, %113, %114, %115, %116, %117, %118, %119, %120, %121, %122, %123, %124, %125, %126, %127}, %128, %129, p, 1, 1, 0, 1;\n}\n"
        : "+f"(d[0]), "+f"(d[1]), "+f"(d[2]), "+f"(d[3]), "+f"(d[4]), "+f"(d[5]), "+f"(d[6]), "+f"(d[7]), "+f"(d[8]), "+f"(d[9]), "+f"(d[10]), "+f"(d[11]), "+f"(d[12]), "+f"(d[13]), "+f"(d[14]), "+f"(d[15]), "+f"(d[16]), "+f"(d[17]), "+f"(d[18]), "+f"(d[19]), "+f"(d[20]), "+f"(d[21]), "+f"(d[22]), "+f"(d[23]), "+f"(d[24]), "+f"(d[25]), "+f"(d[26]), "+f"(d[27]), "+f"(d[28]), "+f"(d[29]), "+f"(d[30]), "+f"(d[31]), "+f"(d[32]), "+f"(d[33]), "+f"(d[34]), "+f"(d[35]), "+f"(d[36]), "+f"(d[37]), "+f"(d[38]), "+f"(d[39]), "+f"(d[40]), "+f"(d[41]), "+f"(d[42]), "+f"(d[43]), "+f"(d[44]), "+f"(d[45]), "+f"(d[46]), "+f"(d[47]), "+f"(d[48]), "+f"(d[49]), "+f"(d[50]), "+f"(d[51]), "+f"(d[52]), "+f"(d[53]), "+f"(d[54]), "+f"(d[55]), "+f"(d[56]), "+f"(d[57]), "+f"(d[58]), "+f"(d[59]), "+f"(d[60]), "+f"(d[61]), "+f"(d[62]), "+f"(d[63]), "+f"(d[64]), "+f"(d[65]), "+f"(d[66]), "+f"(d[67]), "+f"(d[68]), "+f"(d[69]), "+f"(d[70]), "+f"(d[71]), "+f"(d[72]), "+f"(d[73]), "+f"(d[74]), "+f"(d[75]), "+f"(d[76]), "+f"(d[77]), "+f"(d[78]), "+f"(d[79]), "+f"(d[80]), "+f"(d[81]), "+f"(d[82]), "+f"(d[83]), "+f"(d[84]), "+f"(d[85]), "+f"(d[86]), "+f"(d[87]), "+f"(d[88]), "+f"(d[89]), "+f"(d[90]), "+f"(d[91]), "+f"(d[92]), "+f"(d[93]), "+f"(d[94]), "+f"(d[95]), "+f"(d[96]), "+f"(d[97]), "+f"(d[98]), "+f"(d[99]), "+f"(d[100]), "+f"(d[101]), "+f"(d[102]), "+f"(d[103]), "+f"(d[104]), "+f"(d[105]), "+f"(d[106]), "+f"(d[107]), "+f"(d[108]), "+f"(d[109]), "+f"(d[110]), "+f"(d[111]), "+f"(d[112]), "+f"(d[113]), "+f"(d[114]), "+f"(d[115]), "+f"(d[116]), "+f"(d[117]), "+f"(d[118]), "+f"(d[119]), "+f"(d[120]), "+f"(d[121]), "+f"(d[122]), "+f"(d[123]), "+f"(d[124]), "+f"(d[125]), "+f"(d[126]), "+f"(d[127])
        : "l"(da), "l"(db), "r"(scale_d));
}
__device__ __forceinline__ void wgmma_ss_n128(float (&d)[64], uint64_t da, uint64_t db, int scale_d) {
    asm volatile("{\n.reg .pred p;\nsetp.ne.b32 p, %66, 0;\n"
        "wgmma.mma_async.sync.aligned.m64n128k16.f32.bf16.bf16 {%0, %1, %2, %3, %4, %5, %6, %7, %8, %9, %10, %11, %12, %13, %14, %15, %16, %17, %18, %19, %20, %21, %22, %23, %24, %25, %26, %27, %28, %29, %30, %31, %32, %33, %34, %35, %36, %37, %38, %39, %40, %41, %42, %43, %44, %45, %46, %47, %48, %49, %50, %51, %52, %53, %54, %55, %56, %57, %58, %59, %60, %61, %62, %63}, %64, %65, p, 1, 1, 0, 0;\n}\n"
        : "+f"(d[0]), "+f"(d[1]), "+f"(d[2]), "+f"(d[3]), "+f"(d[4]), "+f"(d[5]), "+f"(d[6]), "+f"(d[7]), "+f"(d[8]), "+f"(d[9]), "+f"(d[10]), "+f"(d[11]), "+f"(d[12]), "+f"(d[13]), "+f"(d[14]), "+f"(d[15]), "+f"(d[16]), "+f"(d[17]), "+f"(d[18]), "+f"(d[19]), "+f"(d[20]), "+f"(d[21]), "+f"(d[22]), "+f"(d[23]), "+f"(d[24]), "+f"(d[25]), "+f"(d[26]), "+f"(d[27]), "+f"(d[28]), "+f"(d[29]), "+f"(d[30]), "+f"(d[31]), "+f"(d[32]), "+f"(d[33]), "+f"(d[34]), "+f"(d[35]), "+f"(d[36]), "+f"(d[37]), "+f"(d[38]), "+f"(d[39]), "+f"(d[40]), "+f"(d[41]), "+f"(d[42]), "+f"(d[43]), "+f"(d[44]), "+f"(d[45]), "+f"(d[46]), "+f"(d[47]), "+f"(d[48]), "+f"(d[49]), "+f"(d[50]), "+f"(d[51]), "+f"(d[52]), "+f"(d[53]), "+f"(d[54]), "+f"(d[55]), "+f"(d[56]), "+f"(d[57]), "+f"(d[58]), "+f"(d[59]), "+f"(d[60]), "+f"(d[61]), "+f"(d[62]), "+f"(d[63])
        : "l"(da), "l"(db), "r"(scale_d));
}
__device__ __forceinline__ void wgmma_ss_n64(float (&d)[32], uint64_t da, uint64_t db, int scale_d) {
    asm volatile("{\n.reg .pred p;\nsetp.ne.b32 p, %34, 0;\n"
        "wgmma.mma_async.sync.aligned.m64n64k16.f32.bf16.bf16 {%0, %1, %2, %3, %4, %5, %6, %7, %8, %9, %10, %11, %12, %13, %14, %15, %16, %17, %18, %19, %20, %21, %22, %23, %24, %25, %26, %27, %28, %29, %30, %31}, %32, %33, p, 1, 1, 0, 0;\n}\n"
        : "+f"(d[0]), "+f"(d[1]), "+f"(d[2]), "+f"(d[3]), "+f"(d[4]), "+f"(d[5]), "+f"(d[6]), "+f"(d[7]), "+f"(d[8]), "+f"(d[9]), "+f"(d[10]), "+f"(d[11]), "+f"(d[12]), "+f"(d[13]), "+f"(d[14]), "+f"(d[15]), "+f"(d[16]), "+f"(d[17]), "+f"(d[18]), "+f"(d[19]), "+f"(d[20]), "+f"(d[21]), "+f"(d[22]), "+f"(d[23]), "+f"(d[24]), "+f"(d[25]), "+f"(d[26]), "+f"(d[27]), "+f"(d[28]), "+f"(d[29]), "+f"(d[30]), "+f"(d[31])
        : "l"(da), "l"(db), "r"(scale_d));
}
__device__ __forceinline__ void wgmma_rs_n40_tb(float (&d)[20], uint32_t a0, uint32_t a1, uint32_t a2, uint32_t a3, uint64_t db, int scale_d) {
    asm volatile("{\n.reg .pred p;\nsetp.ne.b32 p, %25, 0;\n"
        "wgmma.mma_async.sync.aligned.m64n40k16.f32.bf16.bf16 {%0, %1, %2, %3, %4, %5, %6, %7, %8, %9, %10, %11, %12, %13, %14, %15, %16, %17, %18, %19}, {%20, %21, %22, %23}, %24, p, 1, 1, 1;\n}\n"
        : "+f"(d[0]), "+f"(d[1]), "+f"(d[2]), "+f"(d[3]), "+f"(d[4]), "+f"(d[5]), "+f"(d[6]), "+f"(d[7]), "+f"(d[8]), "+f"(d[9]), "+f"(d[10]), "+f"(d[11]), "+f"(d[12]), "+f"(d[13]), "+f"(d[14]), "+f"(d[15]), "+f"(d[16]), "+f"(d[17]), "+f"(d[18]), "+f"(d[19])
        : "r"(a0), "r"(a1), "r"(a2), "r"(a3), "l"(db), "r"(scale_d));
}

template <int N> struct WgmmaSSTB;
template <> struct WgmmaSSTB<64> { static __device__ __forceinline__ void run(float (&d)[32], uint64_t a, uint64_t b, int s) { wgmma_ss_n64_tb(d, a, b, s); } };
template <> struct WgmmaSSTB<128> { static __device__ __forceinline__ void run(float (&d)[64], uint64_t a, uint64_t b, int s) { wgmma_ss_n128_tb(d, a, b, s); } };
template <> struct WgmmaSSTB<192> { static __device__ __forceinline__ void run(float (&d)[96], uint64_t a, uint64_t b, int s) { wgmma_ss_n192_tb(d, a, b, s); } };
template <> struct WgmmaSSTB<224> { static __device__ __forceinline__ void run(float (&d)[112], uint64_t a, uint64_t b, int s) { wgmma_ss_n224_tb(d, a, b, s); } };
template <> struct WgmmaSSTB<256> { static __device__ __forceinline__ void run(float (&d)[128], uint64_t a, uint64_t b, int s) { wgmma_ss_n256_tb(d, a, b, s); } };

__global__ void __launch_bounds__(256) ln_kernel(const bf16* __restrict__ in, bf16* __restrict__ out) {
    const int warp = threadIdx.x >> 5, lane = threadIdx.x & 31;
    const int row = blockIdx.x * 8 + warp;
    pdl_launch_dependents();
    pdl_wait();
    const uint4* p = reinterpret_cast<const uint4*>(in + (size_t)row * DM);
    uint4 v[4];
#pragma unroll
    for (int i = 0; i < 4; i++) v[i] = p[lane + 32 * i];
    float f[32];
#pragma unroll
    for (int i = 0; i < 4; i++) {
        const uint32_t w[4] = {v[i].x, v[i].y, v[i].z, v[i].w};
#pragma unroll
        for (int j = 0; j < 4; j++) {
            f[i * 8 + j * 2] = bf16_lo(w[j]);
            f[i * 8 + j * 2 + 1] = bf16_hi(w[j]);
        }
    }
    float s = 0.f;
#pragma unroll
    for (int i = 0; i < 32; i++) s += f[i];
#pragma unroll
    for (int o = 16; o > 0; o >>= 1) s += __shfl_xor_sync(0xffffffffu, s, o);
    const float mean = s * (1.0f / DM);
    float q = 0.f;
#pragma unroll
    for (int i = 0; i < 32; i++) { const float d = f[i] - mean; q += d * d; }
#pragma unroll
    for (int o = 16; o > 0; o >>= 1) q += __shfl_xor_sync(0xffffffffu, q, o);
    const float rstd = 1.0f / sqrtf(q * (1.0f / DM) + 1e-5f);
    uint4* d = reinterpret_cast<uint4*>(out + (size_t)row * DM);
#pragma unroll
    for (int i = 0; i < 4; i++) {
        uint4 w;
        w.x = pack_bf16((f[i * 8 + 0] - mean) * rstd, (f[i * 8 + 1] - mean) * rstd);
        w.y = pack_bf16((f[i * 8 + 2] - mean) * rstd, (f[i * 8 + 3] - mean) * rstd);
        w.z = pack_bf16((f[i * 8 + 4] - mean) * rstd, (f[i * 8 + 5] - mean) * rstd);
        w.w = pack_bf16((f[i * 8 + 6] - mean) * rstd, (f[i * 8 + 7] - mean) * rstd);
        d[lane + 32 * i] = w;
    }
}

enum { EPI_QKV = 0, EPI_RESID = 1, EPI_GELU = 2, EPI_BIAS_RESID = 3 };

template <int BN_, int STAGES_, int EPI_>
struct GemmCfg {
    static constexpr int BM = 128, BK = 64, BN = BN_, STAGES = STAGES_, EPI = EPI_;
    static constexpr int A_BYTES = BM * BK * 2;
    static constexpr int B_CHUNKS = (BN + 63) / 64;
    static constexpr int B_BYTES = B_CHUNKS * BK * 64 * 2;
    static constexpr int STAGE_BYTES = A_BYTES + B_BYTES;
    static constexpr bool HAS_RESID = (EPI == EPI_RESID || EPI == EPI_BIAS_RESID);
    static constexpr bool HAS_BIAS = (EPI == EPI_GELU || EPI == EPI_BIAS_RESID);
    static constexpr int STG_BYTES = HAS_RESID ? BM * BN * 2 : 8 * 2048;
    static constexpr int BAR_BYTES = 256;
    static constexpr int SMEM_BYTES = STAGES * STAGE_BYTES + STG_BYTES + BAR_BYTES + 1024;
    static_assert(SMEM_BYTES <= 232448, "shared memory budget");
};

__device__ __forceinline__ float gelu_tanh(float x) {
    const float u = x * fmaf(0.0356774081f, x * x, 0.7978845608f);
    float t;
    asm("tanh.approx.f32 %0, %1;" : "=f"(t) : "f"(u));
    const float hx = 0.5f * x;
    return fmaf(hx, t, hx);
}

template <class C>
__global__ void __launch_bounds__(384, 1)
gemm_kernel(const __grid_constant__ CUtensorMap tmA, const __grid_constant__ CUtensorMap tmB,
            const __grid_constant__ CUtensorMap tmC, const __grid_constant__ CUtensorMap tmR,
            const bf16* __restrict__ bias, bf16* __restrict__ out_img, int num_m_blk, int num_n_blk, int k_tiles) {
    extern __shared__ uint8_t smem_raw[];
    const uint32_t smem_base = (smem_u32(smem_raw) + 1023) & ~1023u;
    const uint32_t stg_base = smem_base + C::STAGES * C::STAGE_BYTES;
    const uint32_t bar_base = stg_base + C::STG_BYTES;
    auto full_bar = [&](int s) { return bar_base + 8 * s; };
    auto empty_bar = [&](int s) { return bar_base + 8 * (C::STAGES + s); };
    const uint32_t stg_full = bar_base + 8 * (2 * C::STAGES);
    const uint32_t stg_empty = bar_base + 8 * (2 * C::STAGES + 1);

    const int wg = threadIdx.x >> 7;
    const int warp = (threadIdx.x >> 5) & 3;
    const int lane = threadIdx.x & 31;
    const int num_tiles = num_m_blk * num_n_blk;
    if (threadIdx.x == 128) TL(C::EPI, 0);
    pdl_launch_dependents();

    if (threadIdx.x == 0) {
        for (int s = 0; s < C::STAGES; s++) {
            mbar_init(full_bar(s), 1);
            mbar_init(empty_bar(s), 8);
        }
        mbar_init(stg_full, 1);
        mbar_init(stg_empty, 2);
        fence_mbar_init();
        prefetch_tmap(&tmA);
        prefetch_tmap(&tmB);
        if (C::EPI != EPI_QKV) prefetch_tmap(&tmC);
        if (C::HAS_RESID) prefetch_tmap(&tmR);
    }
    __syncthreads();

    if (wg == 0) {
        reg_dealloc<40>();
        if (warp == 0 && lane == 0) {
            int stage = 0;
            uint32_t phase = 0;
            uint32_t stg_phase = 0;
            {
                const int n0 = ((int)blockIdx.x / num_m_blk) * C::BN;
                for (int kt = 0; kt < C::STAGES; kt++) {
                    mbar_expect_tx(full_bar(kt), C::STAGE_BYTES);
#pragma unroll
                    for (int j = 0; j < C::B_CHUNKS; j++)
                        tma_load_2d(smem_base + kt * C::STAGE_BYTES + C::A_BYTES + j * 8192, &tmB, n0 + j * 64, kt * C::BK, full_bar(kt));
                }
                pdl_wait();
            }
            for (int tile = blockIdx.x; tile < num_tiles; tile += gridDim.x) {
                const int m_blk = tile % num_m_blk, n_blk = tile / num_m_blk;
                const int m0 = m_blk * C::BM, n0 = n_blk * C::BN;
                for (int kt = 0; kt < k_tiles; kt++) {
                    const bool preloaded = (tile == (int)blockIdx.x) && (kt < C::STAGES);
                    const uint32_t sa = smem_base + stage * C::STAGE_BYTES;
                    if (!preloaded) {
                        mbar_wait(empty_bar(stage), phase ^ 1);
                        mbar_expect_tx(full_bar(stage), C::STAGE_BYTES);
                    }
                    tma_load_2d(sa, &tmA, kt * C::BK, m0, full_bar(stage));
                    if (!preloaded) {
#pragma unroll
                        for (int j = 0; j < C::B_CHUNKS; j++)
                            tma_load_2d(sa + C::A_BYTES + j * 8192, &tmB, n0 + j * 64, kt * C::BK, full_bar(stage));
                    }
                    if (++stage == C::STAGES) { stage = 0; phase ^= 1; }
                }
                if (C::HAS_RESID) {
                    mbar_wait(stg_empty, stg_phase ^ 1);
                    mbar_expect_tx(stg_full, C::STG_BYTES);
#pragma unroll
                    for (int j = 0; j < C::BN / 64; j++)
                        tma_load_2d(stg_base + j * (128 * 128), &tmR, n0 + j * 64, m0, stg_full);
                    stg_phase ^= 1;
                }
            }
        }
    } else {
        reg_alloc<232>();
        const int cw = wg - 1;
        float acc[C::BN / 2];
        int stage = 0;
        uint32_t phase = 0;
        uint32_t stg_phase = 0;
        bool pending_release = false;
        int tl_slot = 1;
        const uint64_t descA0 = make_desc(smem_base + cw * 64 * 128, 16, 1024, 1);
        const uint64_t descB0 = make_desc(smem_base + C::A_BYTES, 64 * 128  , 1024  , 1);

        for (int tile = blockIdx.x; tile < num_tiles; tile += gridDim.x) {
            const int m_blk = tile % num_m_blk, n_blk = tile / num_m_blk;
            const int m0 = m_blk * C::BM, n0 = n_blk * C::BN;
            int prev_stage = 0;
            uint32_t bias_r[C::HAS_BIAS ? C::BN / 8 : 1];
            if (C::HAS_BIAS) {
#pragma unroll
                for (int b = 0; b < C::BN / 8; b++) bias_r[b] = __ldg(reinterpret_cast<const uint32_t*>(bias + n0 + b * 8 + (lane & 3) * 2));
            }
            for (int kt = 0; kt < k_tiles; kt++) {
                mbar_wait(full_bar(stage), phase);
                if (threadIdx.x == 128 && kt == 0) { TL(C::EPI, tl_slot); tl_slot++; }
                const uint64_t da = descA0 + (uint64_t)((stage * C::STAGE_BYTES) >> 4);
                const uint64_t db = descB0 + (uint64_t)((stage * C::STAGE_BYTES) >> 4);
                wgmma_fence();
#pragma unroll
                for (int k = 0; k < 4; k++)
                    WgmmaSSTB<C::BN>::run(acc, da + k * 2, db + k * 128, (kt > 0 || k > 0) ? 1 : 0);
                wgmma_commit();
                if (kt > 0) {
                    wgmma_wait<1>();
                    if (lane == 0) mbar_arrive(empty_bar(prev_stage));
                }
                if (C::HAS_RESID && pending_release && kt == 1) {
                    if (warp == 0 && lane == 0) {
                        bulk_wait_read0();
                        mbar_arrive(stg_empty);
                    }
                    pending_release = false;
                }
                prev_stage = stage;
                if (++stage == C::STAGES) { stage = 0; phase ^= 1; }
            }
            wgmma_wait<0>();
            if (lane == 0) mbar_arrive(empty_bar(prev_stage));
            if (threadIdx.x == 128) { TL(C::EPI, tl_slot); tl_slot++; }

            const int row_w = warp * 16;
            if (!C::HAS_RESID) {
                const uint32_t wstg = stg_base + (cw * 4 + warp) * 2048;
                const int r = (lane & 7) + ((lane >> 3) & 1) * 8;
                const int row0 = m0 + cw * 64 + row_w;
#pragma unroll
                for (int c = 0; c < C::BN / 32; c++) {
                    const uint32_t buf = wstg + (c & 1) * 1024;
                    if (lane == 0) bulk_wait_read<1>();
                    __syncwarp();
#pragma unroll
                    for (int hh = 0; hh < 2; hh++) {
                        const int c16 = 2 * c + hh;
                        float v[8];
#pragma unroll
                        for (int i = 0; i < 8; i++) v[i] = acc[8 * c16 + i];
                        if (C::HAS_BIAS) {
                            const uint32_t b0 = bias_r[2 * c16], b1 = bias_r[2 * c16 + 1];
                            v[0] += bf16_lo(b0); v[1] += bf16_hi(b0); v[2] += bf16_lo(b0); v[3] += bf16_hi(b0);
                            v[4] += bf16_lo(b1); v[5] += bf16_hi(b1); v[6] += bf16_lo(b1); v[7] += bf16_hi(b1);
                        }
                        if (C::EPI == EPI_GELU) {
#pragma unroll
                            for (int i = 0; i < 8; i++) v[i] = gelu_tanh(v[i]);
                        }
                        const int chunk = hh * 2 + (lane >> 4);
                        stmatrix_x4(buf + r * 64 + ((chunk ^ ((r >> 1) & 3)) << 4),
                                    pack_bf16(v[0], v[1]), pack_bf16(v[2], v[3]), pack_bf16(v[4], v[5]), pack_bf16(v[6], v[7]));
                    }
                    fence_proxy_async();
                    __syncwarp();
                    if (lane == 0) {
                        if (C::EPI == EPI_QKV) {
                            const int colg = (n0 >> 5) + c;
                            const int sel = colg >> 5, head = colg & 31;
                            const size_t dst = (sel == 0) ? ((size_t)head * SEQ + row0) * DH
                                                          : (size_t)NH * SEQ * DH + ((((size_t)head * (SEQ / 128) + m_blk) * 2 + (sel - 1)) * 128 + cw * 64 + row_w) * DH;
                            bulk_store(out_img + dst, buf, 1024);
                        } else {
                            tma_store_2d(&tmC, n0 + c * 32, row0, buf);
                        }
                        bulk_commit();
                    }
                }
            } else {
                mbar_wait(stg_full, stg_phase);
                stg_phase ^= 1;
                const int r0 = cw * 64 + row_w + (lane >> 2);
                const int r1 = r0 + 8;
#pragma unroll
                for (int b = 0; b < C::BN / 8; b++) {
                    const uint32_t box = stg_base + (b >> 3) * (128 * 128);
                    const int chunk = b & 7;
                    const uint32_t a0 = box + r0 * 128 + ((chunk ^ (r0 & 7)) << 4) + (lane & 3) * 4;
                    const uint32_t a1 = box + r1 * 128 + ((chunk ^ (r1 & 7)) << 4) + (lane & 3) * 4;
                    const uint32_t x0 = lds32(a0), x1 = lds32(a1);
                    float v0 = acc[4 * b + 0] + bf16_lo(x0), v1 = acc[4 * b + 1] + bf16_hi(x0);
                    float v2 = acc[4 * b + 2] + bf16_lo(x1), v3 = acc[4 * b + 3] + bf16_hi(x1);
                    if (C::HAS_BIAS) {
                        const uint32_t bb = bias_r[b];
                        v0 += bf16_lo(bb); v1 += bf16_hi(bb); v2 += bf16_lo(bb); v3 += bf16_hi(bb);
                    }
                    sts32(a0, pack_bf16(v0, v1));
                    sts32(a1, pack_bf16(v2, v3));
                }
                fence_proxy_async();
                named_bar_sync_dyn(1 + cw, 128);
                if (warp == 0 && lane == 0) {
#pragma unroll
                    for (int j = 0; j < C::BN / 64; j++)
                        tma_store_2d(&tmC, n0 + j * 64, m0 + cw * 64, stg_base + j * (128 * 128) + cw * 64 * 128);
                    bulk_commit();
                }
                pending_release = true;
            }
            if (threadIdx.x == 128) { TL(C::EPI, tl_slot); tl_slot++; }
        }
        if (lane == 0) bulk_wait0();
        if (threadIdx.x == 128) { TL(C::EPI, tl_slot); tl_slot++; }
    }
}

constexpr int ATT_NST = 4;
constexpr int ATT_LOOKAHEAD = 2;
constexpr int ATT_Q_OFF = 0;
constexpr int ATT_KV_OFF = 2 * 16384;
constexpr int ATT_ONES_OFF = ATT_KV_OFF + ATT_NST * 16384;
constexpr int ATT_O_OFF = ATT_ONES_OFF + 8192;
constexpr int ATT_BAR_OFF = ATT_O_OFF + 4 * 4096;
constexpr int ATT_ZERO_OFF = ATT_BAR_OFF + 192;
constexpr int ATT_SMEM_BYTES = ATT_BAR_OFF + 256 + 1024;
constexpr int ATT_UNITS = NH * (SEQ / 256);
constexpr int ATT_BLOCKS = SEQ / 128;
#define ATT_HANDOFF_V 10
constexpr int ATT_HANDOFF = ATT_HANDOFF_V;
constexpr int ATT_TOKEN_BAR = 5;

template <int N> __device__ __forceinline__ void fence_regs(float (&r)[N]) {
#pragma unroll
    for (int i = 0; i < N; i++) asm volatile("" : "+f"(r[i])::"memory");
}

__device__ __forceinline__ void att_rowmax(const float (&s)[64], float& mx0, float& mx1) {
    float a[4], b[4];
#pragma unroll
    for (int t = 0; t < 4; t++) {
        a[t] = fmaxf(s[4 * t], s[4 * t + 1]);
        b[t] = fmaxf(s[4 * t + 2], s[4 * t + 3]);
    }
#pragma unroll
    for (int g = 1; g < 4; g++) {
#pragma unroll
        for (int t = 0; t < 4; t++) {
            const int i = 16 * g + 4 * t;
            a[t] = fmaxf(a[t], fmaxf(s[i], s[i + 1]));
            b[t] = fmaxf(b[t], fmaxf(s[i + 2], s[i + 3]));
        }
    }
    mx0 = fmaxf(fmaxf(a[0], a[1]), fmaxf(a[2], a[3]));
    mx1 = fmaxf(fmaxf(b[0], b[1]), fmaxf(b[2], b[3]));
    mx0 = fmaxf(mx0, __shfl_xor_sync(0xffffffffu, mx0, 1));
    mx1 = fmaxf(mx1, __shfl_xor_sync(0xffffffffu, mx1, 1));
    mx0 = fmaxf(mx0, __shfl_xor_sync(0xffffffffu, mx0, 2));
    mx1 = fmaxf(mx1, __shfl_xor_sync(0xffffffffu, mx1, 2));
}

__device__ __forceinline__ void att_produce(uint32_t smem_base, uint32_t bar_base, const bf16* gkv, int bidx) {
    const int u = blockIdx.x + (bidx / ATT_BLOCKS) * gridDim.x;
    const int slot = bidx % ATT_NST;
    const uint32_t full = bar_base + 8 * (4 + slot);
    mbar_wait(bar_base + 8 * (4 + ATT_NST + slot), ((bidx / ATT_NST) & 1) ^ 1);
    mbar_expect_tx(full, 16384);
    bulk_load(smem_base + ATT_KV_OFF + slot * 16384, gkv + ((size_t)(u >> 3) * ATT_BLOCKS + (bidx % ATT_BLOCKS)) * (2 * 128 * DH), 16384, full);
}

__global__ void __launch_bounds__(512, 1)
attn_kernel(const bf16* __restrict__ qkv, const __grid_constant__ CUtensorMap tmO) {
    extern __shared__ uint8_t smem_raw[];
    const uint32_t smem_base = (smem_u32(smem_raw) + 1023) & ~1023u;
    const uint32_t bar_base = smem_base + ATT_BAR_OFF;
    auto q_full = [&](int b) { return bar_base + 8 * b; };
    auto q_empty = [&](int b) { return bar_base + 8 * (2 + b); };
    auto kv_full = [&](int s) { return bar_base + 8 * (4 + s); };
    auto kv_empty = [&](int s) { return bar_base + 8 * (4 + ATT_NST + s); };

    const int cw = threadIdx.x >> 7;
    const int warp = (threadIdx.x >> 5) & 3;
    const int lane = threadIdx.x & 31;
    const int wid = threadIdx.x >> 5;

    if (threadIdx.x == 0) {
        for (int b = 0; b < 2; b++) { mbar_init(q_full(b), 1); mbar_init(q_empty(b), 16); }
        for (int s = 0; s < ATT_NST; s++) { mbar_init(kv_full(s), 1); mbar_init(kv_empty(s), 16); }
        fence_mbar_init();
        prefetch_tmap(&tmO);
        sts32(smem_base + ATT_ZERO_OFF, 0u);
    }
    for (int i = threadIdx.x; i < 8192 / 4; i += 512) sts32(smem_base + ATT_ONES_OFF + i * 4, 0x3F803F80u);
    fence_proxy_async();
    pdl_launch_dependents();
    __syncthreads();
    pdl_wait();

    const bf16* gq = qkv;
    const bf16* gkv = qkv + (size_t)NH * SEQ * DH;
    const int my_units = (ATT_UNITS - (int)blockIdx.x + (int)gridDim.x - 1) / (int)gridDim.x;
    const int total_blocks = my_units * ATT_BLOCKS;

    if (threadIdx.x == 0) {
        mbar_expect_tx(q_full(0), 16384);
        bulk_load(smem_base + ATT_Q_OFF, gq + ((size_t)(blockIdx.x >> 3) * SEQ + (blockIdx.x & 7) * 256) * DH, 16384, q_full(0));
        for (int i = 0; i <= ATT_LOOKAHEAD; i++) att_produce(smem_base, bar_base, gkv, i);
    }
    mbar_wait(kv_full(0), 0);

    if (cw >= 2) named_bar_arrive_dyn(ATT_TOKEN_BAR + cw - 2, 256);

    const float c = 0.17677669529663687f * 1.4426950408889634f;
    float s[64], o[20];
    int bidx = 0;
    int qb = 0; uint32_t qph = 0;

    for (int u = blockIdx.x; u < ATT_UNITS; u += gridDim.x) {
        const int head = u >> 3, qblk = u & 7;
        mbar_wait(q_full(qb), qph);
        const uint64_t dq = make_desc(smem_base + ATT_Q_OFF + qb * 16384 + cw * 4096, 16, 512, 2);
        float m0 = -INFINITY, m1 = -INFINITY;

#pragma unroll 1
        for (int j = 0; j < ATT_BLOCKS; j++, bidx++) {
            const int slot = bidx % ATT_NST;
            const uint32_t kvs = smem_base + ATT_KV_OFF + slot * 16384;
            ATL(0);
            ATL(1);
            {
                const uint64_t dk = make_desc(kvs, 16, 512, 2);
                wgmma_fence();
                wgmma_ss_n128(s, dq, dk, 0);
                wgmma_ss_n128(s, dq + 2, dk + 2, 1);
                wgmma_commit();
                wgmma_wait<0>();
                fence_regs(s);
            }
            ATL(2);
            float mx0, mx1;
            att_rowmax(s, mx0, mx1);
            const float mn0 = fmaxf(m0, mx0), mn1 = fmaxf(m1, mx1);
            const float a0 = ex2((m0 - mn0) * c), a1 = ex2((m1 - mn1) * c);
            m0 = mn0; m1 = mn1;
            ATL(3);
            named_bar_sync_dyn(ATT_TOKEN_BAR + cw, 256);
            ATL(4);
            const uint32_t zero = lds32(smem_base + ATT_ZERO_OFF);
            const float mc0 = mn0 * c + __uint_as_float(zero), mc1 = mn1 * c + __uint_as_float(zero);
#pragma unroll
            for (int b = 0; b < ATT_HANDOFF; b++) {
                s[4 * b] = ex2(fmaf(s[4 * b], c, -mc0));
                s[4 * b + 1] = ex2(fmaf(s[4 * b + 1], c, -mc0));
                s[4 * b + 2] = ex2(fmaf(s[4 * b + 2], c, -mc1));
                s[4 * b + 3] = ex2(fmaf(s[4 * b + 3], c, -mc1));
            }
            named_bar_arrive_dyn(ATT_TOKEN_BAR + ((cw + 2) & 3) + (__float_as_uint(s[4 * ATT_HANDOFF - 1]) & zero), 256);
#pragma unroll
            for (int b = ATT_HANDOFF; b < 16; b++) {
                s[4 * b] = ex2(fmaf(s[4 * b], c, -mc0));
                s[4 * b + 1] = ex2(fmaf(s[4 * b + 1], c, -mc0));
                s[4 * b + 2] = ex2(fmaf(s[4 * b + 2], c, -mc1));
                s[4 * b + 3] = ex2(fmaf(s[4 * b + 3], c, -mc1));
            }
            ATL(5);
#pragma unroll
            for (int b = 0; b < 32; b++) s[b] = __uint_as_float(pack_bf16(s[2 * b], s[2 * b + 1]));
            if (j > 0) {
#pragma unroll
                for (int i = 0; i < 20; i++) o[i] *= ((i & 2) ? a1 : a0);
            }
            {
                const uint32_t vaddr = kvs + 8192;
                const uint64_t dv = make_desc(vaddr, (smem_base + ATT_ONES_OFF) - vaddr, 512, 2);
                ATL(6);
                wgmma_fence();
#pragma unroll
                for (int kk = 0; kk < 8; kk++)
                    wgmma_rs_n40_tb(o, __float_as_uint(s[4 * kk]), __float_as_uint(s[4 * kk + 1]), __float_as_uint(s[4 * kk + 2]),
                                    __float_as_uint(s[4 * kk + 3]), dv + kk * 64, (j > 0 || kk > 0) ? 1 : 0);
                wgmma_commit();
                if (wid == ((bidx + 1) & 15) && lane == 0 && bidx + 1 + ATT_LOOKAHEAD < total_blocks)
                    att_produce(smem_base, bar_base, gkv, bidx + 1 + ATT_LOOKAHEAD);
                if (j == 8 && wid == 5 && lane == 0 && u + (int)gridDim.x < ATT_UNITS) {
                    const int un = u + gridDim.x;
                    mbar_wait(q_empty(qb ^ 1), (qb ? qph : qph ^ 1));
                    mbar_expect_tx(q_full(qb ^ 1), 16384);
                    bulk_load(smem_base + ATT_Q_OFF + (qb ^ 1) * 16384, gq + ((size_t)(un >> 3) * SEQ + (un & 7) * 256) * DH, 16384, q_full(qb ^ 1));
                }
                if (bidx + 1 < total_blocks) mbar_wait(kv_full((bidx + 1) % ATT_NST), ((bidx + 1) / ATT_NST) & 1);
                wgmma_wait<0>();
                fence_regs(o);
            }
            ATL(7);
            if (lane == 0) mbar_arrive(kv_empty(slot));
        }
        if (lane == 0) mbar_arrive(q_empty(qb));
        if (++qb == 2) { qb = 0; qph ^= 1; }

        const float inv0 = 1.0f / o[16], inv1 = 1.0f / o[18];
        const uint32_t stg = smem_base + ATT_O_OFF + cw * 4096;
        if (warp == 0 && lane == 0) bulk_wait_read0();
        named_bar_sync_dyn(1 + cw, 128);
        const int r = warp * 16 + (lane & 7) + ((lane >> 3) & 1) * 8;
#pragma unroll
        for (int c16 = 0; c16 < 2; c16++) {
            const int chunk = c16 * 2 + (lane >> 4);
            const uint32_t addr = stg + r * 64 + ((chunk ^ ((r >> 1) & 3)) << 4);
            stmatrix_x4(addr, pack_bf16(o[8 * c16 + 0] * inv0, o[8 * c16 + 1] * inv0), pack_bf16(o[8 * c16 + 2] * inv1, o[8 * c16 + 3] * inv1),
                        pack_bf16(o[8 * c16 + 4] * inv0, o[8 * c16 + 5] * inv0), pack_bf16(o[8 * c16 + 6] * inv1, o[8 * c16 + 7] * inv1));
        }
        fence_proxy_async();
        named_bar_sync_dyn(1 + cw, 128);
        if (warp == 0 && lane == 0) {
            tma_store_2d(&tmO, head * DH, qblk * 256 + cw * 64, stg);
            bulk_commit();
        }
    }
    if (warp == 0 && lane == 0) bulk_wait0();
}

typedef CUresult (*PFN_encodeTiled_t)(CUtensorMap*, CUtensorMapDataType, cuuint32_t, void*, const cuuint64_t*, const cuuint64_t*,
                                      const cuuint32_t*, const cuuint32_t*, CUtensorMapInterleave, CUtensorMapSwizzle,
                                      CUtensorMapL2promotion, CUtensorMapFloatOOBfill);

PFN_encodeTiled_t get_encode_fn() {
    static PFN_encodeTiled_t fn = nullptr;
    if (!fn) {
        void* p = nullptr;
        cudaDriverEntryPointQueryResult q;
        cudaGetDriverEntryPoint("cuTensorMapEncodeTiled", &p, cudaEnableDefault, &q);
        fn = (PFN_encodeTiled_t)p;
    }
    return fn;
}

CUtensorMap make_map_2d(const void* ptr, uint64_t rows, uint64_t cols, uint64_t pitch, uint32_t box_rows, uint32_t box_cols,
                        CUtensorMapSwizzle sw) {
    CUtensorMap m;
    cuuint64_t dims[2] = {cols, rows};
    cuuint64_t strides[1] = {pitch * 2};
    cuuint32_t box[2] = {box_cols, box_rows};
    cuuint32_t es[2] = {1, 1};
    get_encode_fn()(&m, CU_TENSOR_MAP_DATA_TYPE_BFLOAT16, 2, const_cast<void*>(ptr), dims, strides, box, es,
                    CU_TENSOR_MAP_INTERLEAVE_NONE, sw, CU_TENSOR_MAP_L2_PROMOTION_L2_128B, CU_TENSOR_MAP_FLOAT_OOB_FILL_NONE);
    return m;
}
CUtensorMap make_map_w(const void* ptr, uint64_t K, uint64_t N, uint32_t bn) {
    CUtensorMap m;
    cuuint64_t dims[3] = {64, K, N / 64};
    cuuint64_t strides[2] = {N * 2, 128};
    cuuint32_t box[3] = {64, 64, bn / 64};
    cuuint32_t es[3] = {1, 1, 1};
    get_encode_fn()(&m, CU_TENSOR_MAP_DATA_TYPE_BFLOAT16, 3, const_cast<void*>(ptr), dims, strides, box, es,
                    CU_TENSOR_MAP_INTERLEAVE_NONE, CU_TENSOR_MAP_SWIZZLE_128B, CU_TENSOR_MAP_L2_PROMOTION_L2_128B,
                    CU_TENSOR_MAP_FLOAT_OOB_FILL_NONE);
    return m;
}

template <typename T> T* sym_addr(const T& sym) {
    void* p = nullptr;
    cudaGetSymbolAddress(&p, sym);
    return (T*)p;
}

template <typename... KArgs, typename... Args>
void launch_pdl(void (*kern)(KArgs...), int grid, int block, int smem, cudaStream_t stream, Args&&... args) {
    cudaLaunchConfig_t cfg = {};
    cfg.gridDim = dim3(grid);
    cfg.blockDim = dim3(block);
    cfg.dynamicSmemBytes = smem;
    cfg.stream = stream;
    cudaLaunchAttribute attr[1];
    attr[0].id = cudaLaunchAttributeProgrammaticStreamSerialization;
    attr[0].val.programmaticStreamSerializationAllowed = 1;
    cfg.attrs = attr;
    cfg.numAttrs = 1;
    cudaLaunchKernelEx(&cfg, kern, KArgs(args)...);
}

typedef GemmCfg<192, 5, EPI_QKV> CfgQKV;
typedef GemmCfg<128, 5, EPI_RESID> CfgWO;
typedef GemmCfg<224, 4, EPI_GELU> CfgFF1;
typedef GemmCfg<128, 5, EPI_BIAS_RESID> CfgFF2;

}

extern "C" void kernel_launch(void* const* d_in, const int* in_sizes, int n_in, void* d_out, int out_size) {
    (void)in_sizes; (void)n_in; (void)out_size;
    const bf16* x = (const bf16*)d_in[0];
    const bf16* wqkv = (const bf16*)d_in[1];
    const bf16* wo = (const bf16*)d_in[2];
    const bf16* w1 = (const bf16*)d_in[4];
    const bf16* b1 = (const bf16*)d_in[5];
    const bf16* w2 = (const bf16*)d_in[6];
    const bf16* b2 = (const bf16*)d_in[7];
    bf16* out = (bf16*)d_out;

    static bool attr_done = false;
    if (!attr_done) {
        cudaFuncSetAttribute(gemm_kernel<CfgQKV>, cudaFuncAttributeMaxDynamicSharedMemorySize, CfgQKV::SMEM_BYTES);
        cudaFuncSetAttribute(gemm_kernel<CfgWO>, cudaFuncAttributeMaxDynamicSharedMemorySize, CfgWO::SMEM_BYTES);
        cudaFuncSetAttribute(gemm_kernel<CfgFF1>, cudaFuncAttributeMaxDynamicSharedMemorySize, CfgFF1::SMEM_BYTES);
        cudaFuncSetAttribute(gemm_kernel<CfgFF2>, cudaFuncAttributeMaxDynamicSharedMemorySize, CfgFF2::SMEM_BYTES);
        cudaFuncSetAttribute(attn_kernel, cudaFuncAttributeMaxDynamicSharedMemorySize, ATT_SMEM_BYTES);
        attr_done = true;
    }

    bf16* xn = (bf16*)sym_addr(g_xn);
    bf16* qkv = (bf16*)sym_addr(g_qkv);
    bf16* attn = (bf16*)sym_addr(g_attn);
    bf16* h = (bf16*)sym_addr(g_h);
    bf16* hn = (bf16*)sym_addr(g_hn);
    bf16* g = (bf16*)sym_addr(g_g);

    cudaStream_t stream = cudaStreamPerThread;

    launch_pdl(ln_kernel, SEQ / 8, 256, 0, stream, x, xn);
    {
        CUtensorMap tA = make_map_2d(xn, SEQ, DM, DM, 128, 64, CU_TENSOR_MAP_SWIZZLE_128B);
        CUtensorMap tB = make_map_2d(wqkv, DM, 3 * DM, 3 * DM, 64, 64, CU_TENSOR_MAP_SWIZZLE_128B);
        launch_pdl(gemm_kernel<CfgQKV>, 132, 384, CfgQKV::SMEM_BYTES, stream, tA, tB, tA, tA, nullptr, qkv, SEQ / 128, 3 * DM / CfgQKV::BN, DM / 64);
    }
    {
        CUtensorMap tO = make_map_2d(attn, SEQ, DM, DM, 64, 32, CU_TENSOR_MAP_SWIZZLE_64B);
        launch_pdl(attn_kernel, 132, 512, ATT_SMEM_BYTES, stream, (const bf16*)qkv, tO);
    }
    {
        CUtensorMap tA = make_map_2d(attn, SEQ, DM, DM, 128, 64, CU_TENSOR_MAP_SWIZZLE_128B);
        CUtensorMap tB = make_map_2d(wo, DM, DM, DM, 64, 64, CU_TENSOR_MAP_SWIZZLE_128B);
        CUtensorMap tC = make_map_2d(h, SEQ, DM, DM, 64, 64, CU_TENSOR_MAP_SWIZZLE_128B);
        CUtensorMap tR = make_map_2d(x, SEQ, DM, DM, 128, 64, CU_TENSOR_MAP_SWIZZLE_128B);
        launch_pdl(gemm_kernel<CfgWO>, 128, 384, CfgWO::SMEM_BYTES, stream, tA, tB, tC, tR, nullptr, nullptr, SEQ / 128, DM / CfgWO::BN, DM / 64);
    }
    launch_pdl(ln_kernel, SEQ / 8, 256, 0, stream, (const bf16*)h, hn);
    {
        CUtensorMap tA = make_map_2d(hn, SEQ, DM, DM, 128, 64, CU_TENSOR_MAP_SWIZZLE_128B);
        CUtensorMap tB = make_map_2d(w1, DM, DFF, DFF, 64, 64, CU_TENSOR_MAP_SWIZZLE_128B);
        CUtensorMap tC = make_map_2d(g, SEQ, DFF, DFF, 16, 32, CU_TENSOR_MAP_SWIZZLE_64B);
        launch_pdl(gemm_kernel<CfgFF1>, 132, 384, CfgFF1::SMEM_BYTES, stream, tA, tB, tC, tC, b1, nullptr, SEQ / 128, DFF / CfgFF1::BN, DM / 64);
    }
    {
        CUtensorMap tA = make_map_2d(g, SEQ, DFF, DFF, 128, 64, CU_TENSOR_MAP_SWIZZLE_128B);
        CUtensorMap tB = make_map_2d(w2, DFF, DM, DM, 64, 64, CU_TENSOR_MAP_SWIZZLE_128B);
        CUtensorMap tC = make_map_2d(out, SEQ, DM, DM, 64, 64, CU_TENSOR_MAP_SWIZZLE_128B);
        CUtensorMap tR = make_map_2d(h, SEQ, DM, DM, 128, 64, CU_TENSOR_MAP_SWIZZLE_128B);
        launch_pdl(gemm_kernel<CfgFF2>, 128, 384, CfgFF2::SMEM_BYTES, stream, tA, tB, tC, tR, b2, nullptr, SEQ / 128, DM / CfgFF2::BN, DFF / 64);
    }
}
```
